```python
import torch

def _softmax(x, axis=-1):
    return torch.softmax(x, dim=axis)

def _gelu(x):
    return torch.nn.functional.gelu(x, approximate='tanh')

def _silu(x):
    return torch.nn.functional.silu(x)

def _sigmoid(x):
    return torch.sigmoid(x)

def _layernorm(x, axis=-1, eps=1e-05):
    m = x.mean(dim=axis, keepdim=True)
    v = x.var(dim=axis, keepdim=True, unbiased=False)
    return (x - m) / torch.sqrt(v + eps)

def _scatter_add(tgt, idx, src, axis=0):
    return tgt.clone().index_add_(axis, idx, src)

def _segment_sum(src, seg, n):
    out = torch.zeros((n,) + src.shape[1:], dtype=src.dtype)
    return out.index_add_(0, seg, src)

def _pad(x, pw):
    flat = tuple((v for pair in reversed(pw) for v in pair))
    return torch.nn.functional.pad(x, flat)
kernel_name = 'recurrent_scan__memory_aug_recurrent_mem_tr__mixer_s_mlp__prompt'

def setup_inputs():

    _w = lambda a: (lambda t: t.to(torch.bfloat16) if t.is_floating_point() else t)(torch.as_tensor(a))

    def _A_setup():
        B, S, Dm = (1, 2048, 448)
        H, Dh = (16, 256)
        M, seg = (8, 32)
        seg = min(seg, S)
        S = S // seg * seg
        return {'x': _w((lambda *s: torch.randn(*s, dtype=torch.bfloat16) * 0.05)(B, S, Dm)), 'mem0': _w((lambda *s: torch.randn(*s, dtype=torch.bfloat16) * 0.2)(B, M, Dm)), 'Wq': _w((lambda *s: torch.randn(*s, dtype=torch.bfloat16) * 1.6)(Dm, H, Dh) * Dm ** (-0.5)), 'Wk': _w((lambda *s: torch.randn(*s, dtype=torch.bfloat16) * 1.6)(Dm, H, Dh) * Dm ** (-0.5)), 'Wv': _w((lambda *s: torch.randn(*s, dtype=torch.bfloat16) * 0.2)(Dm, H, Dh) * Dm ** (-0.5)), 'Wo': _w((lambda *s: torch.randn(*s, dtype=torch.bfloat16) * 0.2)(H, Dh, Dm) * (H * Dh) ** (-0.5)), 'seg_len': seg}
    _A_in = _A_setup()

    def _B_setup():
        B, S, D, F = (1, 2048, 448, 1792)
        return {'x': _w((lambda *s: torch.randn(*s, dtype=torch.bfloat16) * 0.05)(B, S, D)), 'w1': _w((lambda *s: torch.randn(*s, dtype=torch.bfloat16) * 3.2)(D, D) * D ** (-0.5)), 'w2': _w((lambda *s: torch.randn(*s, dtype=torch.bfloat16) * 3.2)(D, D) * D ** (-0.5)), 'w3': _w((lambda *s: torch.randn(*s, dtype=torch.bfloat16) * 3.2)(D, F) * D ** (-0.5)), 'w4': _w((lambda *s: torch.randn(*s, dtype=torch.bfloat16) * 3.2)(F, D) * F ** (-0.5))}
    _B_in = _B_setup()
    return {'A_x': _A_in['x'], 'A_mem0': _A_in['mem0'], 'A_Wq': _A_in['Wq'], 'A_Wk': _A_in['Wk'], 'A_Wv': _A_in['Wv'], 'A_Wo': _A_in['Wo'], 'A_seg_len': _A_in['seg_len'], 'B_x': _B_in['x'], 'B_w1': _B_in['w1'], 'B_w2': _B_in['w2'], 'B_w3': _B_in['w3'], 'B_w4': _B_in['w4']}

def reference(A_x, A_mem0, A_Wq, A_Wk, A_Wv, A_Wo, A_seg_len, B_x, B_w1, B_w2, B_w3, B_w4):

    def _A_ref(x, mem0, Wq, Wk, Wv, Wo, seg_len):
        B, S, Dm = x.shape
        H, Dh = (Wq.shape[1], Wq.shape[2])
        M = mem0.shape[1]
        scale = Dh ** (-0.5)
        n_seg = S // seg_len
        L = M + seg_len
        idx = torch.arange(L)
        mask = (idx[:, None] < M) | (idx[:, None] >= idx[None, :])
        mem = mem0
        outs = []
        for s in range(n_seg):
            xs = x[:, s * seg_len:(s + 1) * seg_len, :].clone()
            h = torch.concatenate([mem, xs], axis=1)
            q = torch.einsum('btd,dhe->bhte', h, Wq)
            k = torch.einsum('btd,dhe->bhte', h, Wk)
            v = torch.einsum('btd,dhe->bhte', h, Wv)
            scores = torch.einsum('bhqe,bhke->bhqk', q, k) * scale
            scores = torch.where(mask[None, None], scores, -1000000000.0)
            p = _softmax(scores, axis=-1)
            o = torch.einsum('bhqk,bhke->bhqe', p, v)
            o = torch.einsum('bhte,hed->btd', o, Wo)
            mem = o[:, :M, :].clone()
            outs.append(o[:, M:, :])
        return torch.concatenate(outs, axis=1)

    def _B_ref(x, w1, w2, w3, w4):
        B, S, D = x.shape
        h = _gelu(_layernorm(x, axis=-1) @ w1)
        c = D // 4
        g0 = _pad(h[:, :, 0 * c:1 * c], ((0, 0), (1, 0), (0, 0)))[:, :S, :]
        g1 = _pad(h[:, :, 1 * c:2 * c], ((0, 0), (0, 1), (0, 0)))[:, 1:, :]
        g2 = _pad(h[:, :, 2 * c:3 * c], ((0, 0), (2, 0), (0, 0)))[:, :S, :]
        g3 = _pad(h[:, :, 3 * c:], ((0, 0), (0, 2), (0, 0)))[:, 2:, :]
        hs = torch.concatenate([g0, g1, g2, g3], axis=-1) @ w2
        x1 = x + hs
        h2 = _gelu(_layernorm(x1, axis=-1) @ w3) @ w4
        return x1 + h2
    x = A_x
    xn = _layernorm(x, axis=-1)
    s = _A_ref(xn, A_mem0, A_Wq, A_Wk, A_Wv, A_Wo, A_seg_len)
    g = _silu(_B_ref(xn, B_w1, B_w2, B_w3, B_w4))
    return x + s * g
```

```cpp
#include <cuda_runtime.h>
#include <cuda_bf16.h>
#include <cuda.h>
#include <stdint.h>

#define DEVI __device__ __forceinline__

constexpr int SEQ = 2048, DM = 448, NH = 16, DH = 256, NSEG = 64;
constexpr int NCTA = 112;
constexpr uint32_t SENT = 0xFFFFFFFFu;
constexpr long long TIMEOUT = 2000000000LL;
constexpr float C2 = 0.0625f * 1.4426950408889634f;

__device__ __align__(1024) __nv_bfloat16 g_xn[SEQ * DM];
__device__ __align__(1024) __nv_bfloat16 g_s[SEQ * DM];
__device__ __align__(1024) float g_sacc[NSEG * NH * 8 * 128];
__device__ __align__(1024) uint32_t g_scnt[NSEG * NH * 2];
__device__ __align__(8192) unsigned char g_pool[(8 + NH * 6) * 8192];
__device__ uint32_t g_gridbar;

DEVI uint32_t smem_u32(const void* p) { return (uint32_t)__cvta_generic_to_shared(p); }
DEVI void fail(int code) {
  __trap();
}
DEVI void mbar_init(uint32_t a, uint32_t c) { asm volatile("mbarrier.init.shared::cta.b64 [%0], %1;" ::"r"(a), "r"(c) : "memory"); }
DEVI void mbar_expect(uint32_t a, uint32_t tx) { asm volatile("mbarrier.arrive.expect_tx.shared::cta.b64 _, [%0], %1;" ::"r"(a), "r"(tx) : "memory"); }
DEVI void mbar_arrive(uint32_t a) { asm volatile("mbarrier.arrive.shared::cta.b64 _, [%0];" ::"r"(a) : "memory"); }
DEVI void mbar_arrive_rem(uint32_t ra) { asm volatile("mbarrier.arrive.shared::cluster.b64 _, [%0];" ::"r"(ra) : "memory"); }
DEVI void mbar_expect_if(bool c, uint32_t a, uint32_t tx) { asm volatile("{.reg .pred p; setp.ne.u32 p, %2, 0; @p mbarrier.arrive.expect_tx.shared::cta.b64 _, [%0], %1;}" ::"r"(a), "r"(tx), "r"((uint32_t)c) : "memory"); }
DEVI void mbar_arrive_if(bool c, uint32_t a) { asm volatile("{.reg .pred p; setp.ne.u32 p, %1, 0; @p mbarrier.arrive.shared::cta.b64 _, [%0];}" ::"r"(a), "r"((uint32_t)c) : "memory"); }
DEVI void mbar_arrive_rem_if(bool c, uint32_t a) { asm volatile("{.reg .pred p; setp.ne.u32 p, %1, 0; @p mbarrier.arrive.shared::cluster.b64 _, [%0];}" ::"r"(a), "r"((uint32_t)c) : "memory"); }
DEVI bool mbar_test(uint32_t a, uint32_t par) {
  uint32_t ok;
  asm volatile("{.reg .pred p; mbarrier.test_wait.parity.shared::cta.b64 p, [%1], %2; selp.u32 %0, 1, 0, p;}" : "=r"(ok) : "r"(a), "r"(par) : "memory");
  return ok;
}
DEVI bool mbar_try(uint32_t a, uint32_t par) {
  uint32_t ok;
  asm volatile("{.reg .pred p; mbarrier.try_wait.parity.shared::cta.b64 p, [%1], %2; selp.u32 %0, 1, 0, p;}" : "=r"(ok) : "r"(a), "r"(par) : "memory");
  return ok;
}
DEVI void mbar_wait(uint32_t a, uint32_t par, int) {
  asm volatile("{\n.reg .pred p;\n.reg .u32 n;\nmov.u32 n, 0;\n"
               "W_LOOP:\nmbarrier.try_wait.parity.shared::cta.b64 p, [%0], %1;\n@p bra.uni W_DONE;\n"
               "add.u32 n, n, 1;\nsetp.lt.u32 p, n, 0x1000000;\n@p bra.uni W_LOOP;\ntrap;\nW_DONE:\n}\n" ::"r"(a), "r"(par) : "memory");
}
DEVI uint32_t mapa(uint32_t a, uint32_t r) { uint32_t o; asm("mapa.shared::cluster.u32 %0, %1, %2;" : "=r"(o) : "r"(a), "r"(r)); return o; }
DEVI void st_async4(uint32_t a, float x, float y, float z, float w, uint32_t mb) {
  asm volatile("st.async.weak.shared::cluster.mbarrier::complete_tx::bytes.v4.f32 [%0], {%1,%2,%3,%4}, [%5];" ::"r"(a), "f"(x), "f"(y), "f"(z), "f"(w), "r"(mb) : "memory");
}
DEVI void st_async1(uint32_t a, uint32_t x, uint32_t mb) {
  asm volatile("st.async.weak.shared::cluster.mbarrier::complete_tx::bytes.b32 [%0], %1, [%2];" ::"r"(a), "r"(x), "r"(mb) : "memory");
}
DEVI void st_async2(uint32_t a, uint32_t x, uint32_t y, uint32_t mb) {
  asm volatile("st.async.weak.shared::cluster.mbarrier::complete_tx::bytes.v2.b32 [%0], {%1,%2}, [%3];" ::"r"(a), "r"(x), "r"(y), "r"(mb) : "memory");
}
#define OPQ(VAR) asm volatile("" : "+r"(VAR))
#define PIN(VAR) VAR = __shfl_sync(0xffffffffu, VAR, threadIdx.x & 31)
DEVI void bar_sync(int id, int n) { asm volatile("bar.sync %0, %1;" ::"r"(id), "r"(n) : "memory"); }
DEVI void bar_arrive(int id, int n) { asm volatile("bar.arrive %0, %1;" ::"r"(id), "r"(n) : "memory"); }
DEVI void cluster_sync() { asm volatile("barrier.cluster.arrive.release.aligned; barrier.cluster.wait.acquire.aligned;" ::: "memory"); }
DEVI void fence_gpu() { asm volatile("fence.acq_rel.gpu;" ::: "memory"); }
DEVI void fence_proxy_smem() { asm volatile("fence.proxy.async.shared::cta;" ::: "memory"); }
DEVI void fence_proxy_all() { asm volatile("fence.proxy.async;" ::: "memory"); }
DEVI uint2 ld_rlx2(const void* p) { uint2 v; asm volatile("ld.relaxed.gpu.global.v2.u32 {%0,%1}, [%2];" : "=r"(v.x), "=r"(v.y) : "l"(p) : "memory"); return v; }
DEVI float4 ld_rlx4f(const void* p) { float4 v; asm volatile("ld.relaxed.gpu.global.v4.f32 {%0,%1,%2,%3}, [%4];" : "=f"(v.x), "=f"(v.y), "=f"(v.z), "=f"(v.w) : "l"(p) : "memory"); return v; }
DEVI uint32_t ld_acq(const void* p) { uint32_t v; asm volatile("ld.acquire.gpu.global.u32 %0, [%1];" : "=r"(v) : "l"(p) : "memory"); return v; }
DEVI void st_rlx(void* p, uint32_t v) { asm volatile("st.relaxed.gpu.global.u32 [%0], %1;" ::"l"(p), "r"(v) : "memory"); }
DEVI void st_rlx2(void* p, uint32_t v, uint32_t w) { asm volatile("st.relaxed.gpu.global.v2.u32 [%0], {%1,%2};" ::"l"(p), "r"(v), "r"(w) : "memory"); }
DEVI void st_rlx2_if(bool c, void* p, uint32_t v, uint32_t w) { asm volatile("{.reg .pred p; setp.ne.u32 p, %3, 0; @p st.relaxed.gpu.global.v2.u32 [%0], {%1,%2};}" ::"l"(p), "r"(v), "r"(w), "r"((uint32_t)c) : "memory"); }
DEVI void red_add4(void* p, float a, float b, float c, float d) { asm volatile("red.relaxed.gpu.global.add.v4.f32 [%0], {%1,%2,%3,%4};" ::"l"(p), "f"(a), "f"(b), "f"(c), "f"(d) : "memory"); }
DEVI float atom_add4(void* p, float a, float b, float c, float d) {
  float o0, o1, o2, o3;
  asm volatile("atom.relaxed.gpu.global.add.v4.f32 {%0,%1,%2,%3}, [%4], {%5,%6,%7,%8};" : "=f"(o0), "=f"(o1), "=f"(o2), "=f"(o3) : "l"(p), "f"(a), "f"(b), "f"(c), "f"(d) : "memory");
  return o0;
}
DEVI uint32_t ld_rlx(const void* p) { uint32_t v; asm volatile("ld.relaxed.gpu.global.u32 %0, [%1];" : "=r"(v) : "l"(p) : "memory"); return v; }
DEVI void red_add_u32(void* p, uint32_t v) { asm volatile("red.relaxed.gpu.global.add.u32 [%0], %1;" ::"l"(p), "r"(v) : "memory"); }
DEVI uint32_t atom_add(void* p, uint32_t v) { uint32_t o; asm volatile("atom.relaxed.gpu.global.add.u32 %0, [%1], %2;" : "=r"(o) : "l"(p), "r"(v) : "memory"); return o; }
DEVI uint32_t pack_bf2(float lo, float hi) { uint32_t r; asm("cvt.rn.bf16x2.f32 %0, %1, %2;" : "=r"(r) : "f"(hi), "f"(lo)); return r; }
DEVI float ex2(float x) { float r; asm("ex2.approx.ftz.f32 %0, %1;" : "=f"(r) : "f"(x)); return r; }
DEVI float rcpf(float x) { float r; asm("rcp.approx.ftz.f32 %0, %1;" : "=f"(r) : "f"(x)); return r; }
DEVI void sts32(uint32_t a, uint32_t v) { asm volatile("st.shared.b32 [%0], %1;" ::"r"(a), "r"(v) : "memory"); }
DEVI void sts64f(uint32_t a, float x, float y) { asm volatile("st.shared.v2.f32 [%0], {%1,%2};" ::"r"(a), "f"(x), "f"(y) : "memory"); }
DEVI float2 lds64f(uint32_t a) { float2 v; asm volatile("ld.shared.v2.f32 {%0,%1}, [%2];" : "=f"(v.x), "=f"(v.y) : "r"(a) : "memory"); return v; }
DEVI float4 lds128f(uint32_t a) { float4 v; asm volatile("ld.shared.v4.f32 {%0,%1,%2,%3}, [%4];" : "=f"(v.x), "=f"(v.y), "=f"(v.z), "=f"(v.w) : "r"(a) : "memory"); return v; }
DEVI void sts128f(uint32_t a, float4 v) { asm volatile("st.shared.v4.f32 [%0], {%1,%2,%3,%4};" ::"r"(a), "f"(v.x), "f"(v.y), "f"(v.z), "f"(v.w) : "memory"); }
DEVI uint2 lds64(uint32_t a) { uint2 v; asm volatile("ld.shared.v2.b32 {%0,%1}, [%2];" : "=r"(v.x), "=r"(v.y) : "r"(a) : "memory"); return v; }
DEVI uint4 lds128(uint32_t a) { uint4 v; asm volatile("ld.shared.v4.b32 {%0,%1,%2,%3}, [%4];" : "=r"(v.x), "=r"(v.y), "=r"(v.z), "=r"(v.w) : "r"(a) : "memory"); return v; }
DEVI void sts128(uint32_t a, uint32_t x, uint32_t y, uint32_t z, uint32_t w) { asm volatile("st.shared.v4.b32 [%0], {%1,%2,%3,%4};" ::"r"(a), "r"(x), "r"(y), "r"(z), "r"(w) : "memory"); }
DEVI void ldsm4(uint32_t& r0, uint32_t& r1, uint32_t& r2, uint32_t& r3, uint32_t a) {
  asm volatile("ldmatrix.sync.aligned.m8n8.x4.shared.b16 {%0,%1,%2,%3}, [%4];" : "=r"(r0), "=r"(r1), "=r"(r2), "=r"(r3) : "r"(a) : "memory");
}
DEVI void stsm4(uint32_t a, uint32_t r0, uint32_t r1, uint32_t r2, uint32_t r3) {
  asm volatile("stmatrix.sync.aligned.m8n8.x4.shared.b16 [%0], {%1,%2,%3,%4};" ::"r"(a), "r"(r0), "r"(r1), "r"(r2), "r"(r3) : "memory");
}
DEVI void stsm2(uint32_t a, uint32_t r0, uint32_t r1) { asm volatile("stmatrix.sync.aligned.m8n8.x2.shared.b16 [%0], {%1,%2};" ::"r"(a), "r"(r0), "r"(r1) : "memory"); }
DEVI void stsm1(uint32_t a, uint32_t r0) { asm volatile("stmatrix.sync.aligned.m8n8.x1.shared.b16 [%0], {%1};" ::"r"(a), "r"(r0) : "memory"); }
DEVI void stsm4t(uint32_t a, uint32_t r0, uint32_t r1, uint32_t r2, uint32_t r3) {
  asm volatile("stmatrix.sync.aligned.m8n8.x4.trans.shared.b16 [%0], {%1,%2,%3,%4};" ::"r"(a), "r"(r0), "r"(r1), "r"(r2), "r"(r3) : "memory");
}
DEVI void stsm2t(uint32_t a, uint32_t r0, uint32_t r1) { asm volatile("stmatrix.sync.aligned.m8n8.x2.trans.shared.b16 [%0], {%1,%2};" ::"r"(a), "r"(r0), "r"(r1) : "memory"); }
DEVI uint32_t movm(uint32_t a) { uint32_t d; asm volatile("movmatrix.sync.aligned.m8n8.trans.b16 %0, %1;" : "=r"(d) : "r"(a)); return d; }
DEVI void mma16(float (&d)[4], uint32_t a0, uint32_t a1, uint32_t a2, uint32_t a3, uint32_t b0, uint32_t b1) {
  asm volatile("mma.sync.aligned.m16n8k16.row.col.f32.bf16.bf16.f32 {%0,%1,%2,%3}, {%4,%5,%6,%7}, {%8,%9}, {%0,%1,%2,%3};"
               : "+f"(d[0]), "+f"(d[1]), "+f"(d[2]), "+f"(d[3]) : "r"(a0), "r"(a1), "r"(a2), "r"(a3), "r"(b0), "r"(b1));
}
DEVI void mma8(float (&d)[4], uint32_t a0, uint32_t a1, uint32_t b0) {
  asm volatile("mma.sync.aligned.m16n8k8.row.col.f32.bf16.bf16.f32 {%0,%1,%2,%3}, {%4,%5}, {%6}, {%0,%1,%2,%3};"
               : "+f"(d[0]), "+f"(d[1]), "+f"(d[2]), "+f"(d[3]) : "r"(a0), "r"(a1), "r"(b0));
}
DEVI void wg_fence() { asm volatile("wgmma.fence.sync.aligned;" ::: "memory"); }
DEVI void wg_commit() { asm volatile("wgmma.commit_group.sync.aligned;" ::: "memory"); }
DEVI void wg_wait0() { asm volatile("wgmma.wait_group.sync.aligned 0;" ::: "memory"); }
constexpr uint32_t SB = 1024;
__host__ __device__ constexpr uint32_t desc_lo(uint32_t off) { return (((SB + off) & 0x3FFFF) >> 4) | (64u << 16); }
DEVI uint64_t mkdesc(uint32_t lo) { uint64_t d; asm("mov.b64 %0, {%1, %2};" : "=l"(d) : "r"(lo), "r"(0x40000040u)); return d; }
template <int TA>
DEVI void wgmma_ss_n32(float (&d)[16], uint64_t da, uint64_t db, int sc) {
  asm volatile("{.reg .pred p; setp.ne.b32 p, %18, 0;\n"
               "wgmma.mma_async.sync.aligned.m64n32k16.f32.bf16.bf16 {%0,%1,%2,%3,%4,%5,%6,%7,%8,%9,%10,%11,%12,%13,%14,%15}, %16, %17, p, 1, 1, %19, 0;}\n"
               : "+f"(d[0]), "+f"(d[1]), "+f"(d[2]), "+f"(d[3]), "+f"(d[4]), "+f"(d[5]), "+f"(d[6]), "+f"(d[7]), "+f"(d[8]), "+f"(d[9]), "+f"(d[10]),
                 "+f"(d[11]), "+f"(d[12]), "+f"(d[13]), "+f"(d[14]), "+f"(d[15])
               : "l"(da), "l"(db), "r"(sc), "n"(TA));
}
DEVI void wgmma_rs_n40(float (&d)[20], const uint32_t* a, uint64_t db, int sc) {
  asm volatile("{.reg .pred p; setp.ne.b32 p, %25, 0;\n"
               "wgmma.mma_async.sync.aligned.m64n40k16.f32.bf16.bf16 {%0,%1,%2,%3,%4,%5,%6,%7,%8,%9,%10,%11,%12,%13,%14,%15,%16,%17,%18,%19}, {%20,%21,%22,%23}, %24, p, 1, 1, 0;}\n"
               : "+f"(d[0]), "+f"(d[1]), "+f"(d[2]), "+f"(d[3]), "+f"(d[4]), "+f"(d[5]), "+f"(d[6]), "+f"(d[7]), "+f"(d[8]), "+f"(d[9]), "+f"(d[10]),
                 "+f"(d[11]), "+f"(d[12]), "+f"(d[13]), "+f"(d[14]), "+f"(d[15]), "+f"(d[16]), "+f"(d[17]), "+f"(d[18]), "+f"(d[19])
               : "r"(a[0]), "r"(a[1]), "r"(a[2]), "r"(a[3]), "l"(db), "r"(sc));
}
DEVI void tma2d(uint32_t dst, const CUtensorMap* tm, int c0, int c1, uint32_t mb) {
  asm volatile("cp.async.bulk.tensor.2d.shared::cluster.global.mbarrier::complete_tx::bytes [%0], [%1, {%3, %4}], [%2];" ::"r"(dst), "l"(tm), "r"(mb), "r"(c0), "r"(c1) : "memory");
}
DEVI void tma2d_mc(uint32_t dst, const CUtensorMap* tm, int c0, int c1, uint32_t mb, uint16_t mask) {
  asm volatile("cp.async.bulk.tensor.2d.shared::cluster.global.mbarrier::complete_tx::bytes.multicast::cluster [%0], [%1, {%3, %4}], [%2], %5;" ::"r"(dst), "l"(tm), "r"(mb), "r"(c0), "r"(c1), "h"(mask) : "memory");
}
DEVI void tma2d_mc_if(bool c, uint32_t dst, const CUtensorMap* tm, int c0, int c1, uint32_t mb, uint16_t mask) {
  asm volatile("{.reg .pred p; setp.ne.u32 p, %6, 0; @p cp.async.bulk.tensor.2d.shared::cluster.global.mbarrier::complete_tx::bytes.multicast::cluster [%0], [%1, {%3, %4}], [%2], %5;}" ::"r"(dst), "l"(tm), "r"(mb), "r"(c0), "r"(c1), "h"(mask), "r"((uint32_t)c) : "memory");
}
template <int N>
DEVI uint32_t delay_clk(uint32_t x, uint32_t zero) {
  if (N >= 40) {
#pragma unroll 1
    for (int i = 0; i < N / 40; i++)
      asm volatile("mad.lo.u32 %0, %0, %1, %0;\nmad.lo.u32 %0, %0, %1, %0;\nmad.lo.u32 %0, %0, %1, %0;\nmad.lo.u32 %0, %0, %1, %0;\nmad.lo.u32 %0, %0, %1, %0;\nmad.lo.u32 %0, %0, %1, %0;" : "+r"(x) : "r"(zero));
  }
  return x;
}
struct True_ { static constexpr bool value = true; };
struct False_ { static constexpr bool value = false; };
DEVI uint32_t tag_of(int s) { return ((s >> 1) & 1) ^ 1; }
DEVI void poll_issue(uint2 (&v)[7], uint32_t off) {
  const unsigned char* p = g_pool + off;
#pragma unroll
  for (int j = 0; j < 7; j++) v[j] = ld_rlx2(p + j * 256);
}
DEVI uint32_t poll_finish(uint2 (&v)[7], uint32_t off, uint32_t tagm) {
  uint32_t nret;
  asm volatile("{\n.reg .pred p;\n.reg .b32 a, b, c, n;\nmov.u32 n, 0;\n"
               "P_CHK:\n"
               "lop3.b32 a, %0, %2, %16, 0x42;\nlop3.b32 b, %4, %6, %16, 0x42;\nlop3.b32 c, %8, %10, %16, 0x42;\n"
               "lop3.b32 a, a, b, c, 0x80;\nlop3.b32 a, a, %12, %16, 0x60;\nand.b32 a, a, 1;\nsetp.ne.u32 p, a, 0;\n"
               "vote.sync.all.pred p, p, 0xffffffff;\n@p bra.uni P_DONE;\n"
               "add.u32 n, n, 1;\nsetp.gt.u32 p, n, 0x400000;\n@p trap;\n"
               "ld.relaxed.gpu.global.v2.u32 {%0,%1}, [%15];\nld.relaxed.gpu.global.v2.u32 {%2,%3}, [%15+256];\n"
               "ld.relaxed.gpu.global.v2.u32 {%4,%5}, [%15+512];\nld.relaxed.gpu.global.v2.u32 {%6,%7}, [%15+768];\n"
               "ld.relaxed.gpu.global.v2.u32 {%8,%9}, [%15+1024];\nld.relaxed.gpu.global.v2.u32 {%10,%11}, [%15+1280];\n"
               "ld.relaxed.gpu.global.v2.u32 {%12,%13}, [%15+1536];\nbra.uni P_CHK;\n"
               "P_DONE:\nmov.u32 %14, n;\n}\n"
               : "+r"(v[0].x), "+r"(v[0].y), "+r"(v[1].x), "+r"(v[1].y), "+r"(v[2].x), "+r"(v[2].y), "+r"(v[3].x), "+r"(v[3].y), "+r"(v[4].x), "+r"(v[4].y),
                 "+r"(v[5].x), "+r"(v[5].y), "+r"(v[6].x), "+r"(v[6].y), "=r"(nret)
               : "l"(g_pool + off), "r"(tagm) : "memory");
  return nret;
}
DEVI float sum7x(const uint2 (&v)[7]) { return ((__uint_as_float(v[0].x) + __uint_as_float(v[1].x)) + (__uint_as_float(v[2].x) + __uint_as_float(v[3].x))) + ((__uint_as_float(v[4].x) + __uint_as_float(v[5].x)) + __uint_as_float(v[6].x)); }
DEVI float sum7y(const uint2 (&v)[7]) { return ((__uint_as_float(v[0].y) + __uint_as_float(v[1].y)) + (__uint_as_float(v[2].y) + __uint_as_float(v[3].y))) + ((__uint_as_float(v[4].y) + __uint_as_float(v[5].y)) + __uint_as_float(v[6].y)); }

constexpr int XSLOT = 35840;
constexpr int OFF_XS = 0;
constexpr int OFF_AG = 71680;
constexpr int OFF_RS = 73728;
constexpr int OFF_BAR = 77824;
constexpr int OFF_U = 78848;
constexpr int OFF_WQ = OFF_U, OFF_WO = OFF_U + 32768, OFF_RING = OFF_U + 65536;
constexpr int OFF_AC = OFF_U;
constexpr int KSLOT = 9216, ZSLOT = 5120;
constexpr int OFF_K = OFF_AC + 57344;
constexpr int OFF_Z = OFF_K + 4 * KSLOT;
constexpr int OFF_OUT = OFF_Z + 6 * ZSLOT;
constexpr int OFF_SMX = OFF_OUT + 16384;
constexpr int OFF_SMM = OFF_SMX + 1280;
constexpr int OFF_PE = OFF_SMM + 1024;
constexpr int SMEM_MAIN = OFF_U + 147456;
static_assert(OFF_PE <= OFF_U + 147456, "smem");
enum { B_XFULL = 0, B_XEMPTY = 2, B_AG = 3, B_RS = 5, B_KFULL = 7, B_KEMPTY = 11, B_WDONE = 16, B_OUTF = 24, B_OUTC = 26, B_WFULL = 29, B_RFULL = 30, B_REMPTY = 35, B_ZFULL = 40, B_ZEMPTY = 46, B_NUM = 52 };
enum { NB_T = 1, NB_MREADY = 2, NB_GO = 3, NB_EX = 4, NB_W0 = 5, NB_PA = 6, NB_START = 7, NB_HELP = 8, NB_GO1 = 9, NB_SM = 10 };
constexpr int NTHR = 512;
#define POLL_AT 11
#define XPW 1
#define T_DELAY 320
#define POLL_DT 130
#define POLL_DT2 190
#define XLIM NSEG
#define TMA_DT 0
#define NPROBE 3
#define PREFETCH 0
#define ROT 0
#define G2_AT 5
#define TPW 0
#define W0_DELAY 160
#define TPOLL_AT 1

#define PROF_INIT(on)
#define PROF(slot, s)
#define PROFS(slot, s)
#define PROFP(i)
#define PROFV(slot, s, v) (void)(v)

DEVI void probe_pages(int hw, int lane, uint32_t h, uint32_t c, uint32_t s_mask) {
#pragma unroll 1
  for (int pi = hw; pi < 10; pi += 6) {
    if (lane == 0) {
      unsigned char* pg = g_pool + (pi < 4 ? 2 * pi + (c & 1) : 8 + h * 6 + (pi - 4)) * 8192 + 1792 + (blockIdx.x & 64) * 32 + (blockIdx.x & 63) * 4;
      st_rlx(pg, 0); st_rlx(pg + 4096, 0);
      int best0 = 1 << 30, best1 = 1 << 30;
#pragma unroll 1
      for (int r = 0; r < NPROBE; r++) {
        const uint32_t a = clock(); uint32_t v = atom_add(pg, 1); if (v == 0x12345678u) fail(1); const uint32_t b = clock();
        v = atom_add(pg + 4096, 1); if (v == 0x12345678u) fail(1); const uint32_t e = clock();
        best0 = min(best0, (int)(b - a)); best1 = min(best1, (int)(e - b));
      }
      if (best1 < best0) asm volatile("red.shared.or.b32 [%0], %1;" ::"r"(s_mask), "r"(1u << pi) : "memory");
    }
    __syncwarp();
  }
}
DEVI void helper_prologue(int hw, int lane, const __nv_bfloat16* __restrict__ xin) {
  uint32_t q[4][7];
#pragma unroll
  for (int k = 0; k < 4; k++) {
    const uint32_t* src = (const uint32_t*)(xin + (size_t)min((int)blockIdx.x + (hw + 5 * k) * NCTA, SEQ - 1) * DM);
#pragma unroll
    for (int i = 0; i < 7; i++) q[k][i] = __ldg(src + i * 32 + lane);
  }
  {
    const int ht = hw * 32 + lane;
    uint4* z = (uint4*)g_sacc;
#pragma unroll 1
    for (int i = blockIdx.x * 160 + ht; i < NSEG * NH * 8 * 32; i += NCTA * 160) z[i] = make_uint4(0, 0, 0, 0);
    if (blockIdx.x < 4) ((uint4*)g_scnt)[min(blockIdx.x * 160 + ht, NSEG * NH * 2 / 4 - 1)] = make_uint4(0, 0, 0, 0);
    uint4* pz = (uint4*)g_pool;
#pragma unroll 1
    for (int i = blockIdx.x * 160 + ht; i < (8 + NH * 6) * 512; i += NCTA * 160) pz[i] = make_uint4(0, 0, 0, 0);
  }
  float v[4][14], sm[4], vs[4];
#pragma unroll
  for (int k = 0; k < 4; k++) {
    sm[k] = 0;
#pragma unroll
    for (int i = 0; i < 7; i++) { v[k][2 * i] = __uint_as_float(q[k][i] << 16); v[k][2 * i + 1] = __uint_as_float(q[k][i] & 0xFFFF0000u); sm[k] += v[k][2 * i] + v[k][2 * i + 1]; }
  }
#pragma unroll
  for (int o = 16; o; o >>= 1)
#pragma unroll
    for (int k = 0; k < 4; k++) sm[k] += __shfl_xor_sync(0xffffffffu, sm[k], o);
#pragma unroll
  for (int k = 0; k < 4; k++) {
    vs[k] = 0;
#pragma unroll
    for (int i = 0; i < 14; i++) { v[k][i] -= sm[k] * (1.0f / DM); vs[k] += v[k][i] * v[k][i]; }
  }
#pragma unroll
  for (int o = 16; o; o >>= 1)
#pragma unroll
    for (int k = 0; k < 4; k++) vs[k] += __shfl_xor_sync(0xffffffffu, vs[k], o);
#pragma unroll
  for (int k = 0; k < 4; k++) {
    const float rs = rsqrtf(vs[k] * (1.0f / DM) + 1e-5f);
    uint32_t* dst = (uint32_t*)(g_xn + (size_t)min((int)blockIdx.x + (hw + 5 * k) * NCTA, SEQ - 1) * DM);
#pragma unroll
    for (int i = 0; i < 7; i++) dst[i * 32 + lane] = pack_bf2(v[k][2 * i] * rs, v[k][2 * i + 1] * rs);
  }
  fence_proxy_all();
  bar_sync(NB_HELP, 224);
}
DEVI void role_exit(uint32_t s_done, int lane, bool watch) {
  __syncwarp();
  if (lane == 0) {
    asm volatile("red.shared.add.u32 [%0], 1;" ::"r"(s_done) : "memory");
    if (watch) {
      long long t0 = clock64();
      while (true) {
        uint32_t dn; asm volatile("ld.volatile.shared.b32 %0, [%1];" : "=r"(dn) : "r"(s_done) : "memory");
        if (dn >= 16) break;
        if (clock64() - t0 > TIMEOUT) fail(303);
      }
    }
  }
  __syncwarp();
  asm volatile("barrier.cluster.arrive.relaxed.aligned; barrier.cluster.wait.aligned;" ::: "memory");
}

__global__ void __launch_bounds__(NTHR, 1)
attn_main(const __grid_constant__ CUtensorMap tmWq, const __grid_constant__ CUtensorMap tmWk, const __grid_constant__ CUtensorMap tmWv,
          const __grid_constant__ CUtensorMap tmWo, const __grid_constant__ CUtensorMap tmX,
          const __nv_bfloat16* __restrict__ xin, const __nv_bfloat16* __restrict__ mem0, int never) {
  extern __shared__ __align__(1024) unsigned char smem_raw[];
  const uint32_t sb = smem_u32(smem_raw);
  if ((sb & 0xFFFFFF) != SB || mapa(sb, 4) != ((4u << 24) | SB)) fail(2);
  const int tid = threadIdx.x, warp = __reduce_min_sync(0xffffffffu, tid >> 5);
  const int lane = tid & 31;
  const int g = lane >> 2, t = lane & 3;
  uint32_t h, c;
  asm("mov.u32 %0, %%cluster_ctarank;" : "=r"(h));
  asm("mov.u32 %0, %%clusterid.x;" : "=r"(c));
  const uint32_t bars = sb + OFF_BAR;
  const uint32_t SBL = sb;
#define BAR(i) (bars + (i) * 8)
  const uint32_t s_mask = bars + 512, s_done = bars + 516;

  if (tid == 0) PROFP(0);
  asm volatile("griddepcontrol.launch_dependents;");
  if (tid == 0) {
    mbar_init(BAR(B_XFULL), 1); mbar_init(BAR(B_XFULL + 1), 1); mbar_init(BAR(B_XEMPTY), 128);
    for (int i = 0; i < 2; i++) { mbar_init(BAR(B_AG + i), 1); mbar_init(BAR(B_RS + i), 1); mbar_init(BAR(B_OUTF + i), 1); mbar_init(BAR(B_OUTC + i), 16); }
    for (int i = 0; i < 4; i++) { mbar_init(BAR(B_KFULL + i), 4); mbar_init(BAR(B_KEMPTY + i), 4); }
    for (int i = 0; i < 6; i++) { mbar_init(BAR(B_ZFULL + i), 4); mbar_init(BAR(B_ZEMPTY + i), 4); }
    mbar_init(BAR(B_WDONE), 4); mbar_init(BAR(B_WDONE + 1), 4);
    for (int i = 0; i < 5; i++) { mbar_init(BAR(B_RFULL + i), 1); mbar_init(BAR(B_REMPTY + i), 4); }
    mbar_init(BAR(B_WFULL), 1);
    sts32(s_mask, 0); sts32(s_done, 0);
    asm volatile("fence.mbarrier_init.release.cluster;" ::: "memory");
    for (int i = 0; i < 2; i++) {
      mbar_expect(BAR(B_XFULL + i), 28672); mbar_expect(BAR(B_AG + i), 1024); mbar_expect(BAR(B_RS + i), 2048); mbar_expect(BAR(B_OUTF + i), 8192);
    }
    mbar_arrive(BAR(B_KEMPTY)); mbar_arrive(BAR(B_KEMPTY)); mbar_arrive(BAR(B_ZEMPTY)); mbar_arrive(BAR(B_ZEMPTY));
  }
  __syncthreads();
  if (warp == 11) {
    if (lane == 0) {
      mbar_expect(BAR(B_WFULL), 65536);
      for (int j = 0; j < 4; j++) {
        tma2d(sb + OFF_WQ + j * 8192, &tmWq, h * DH + j * 64, c * 64, BAR(B_WFULL));
        tma2d(sb + OFF_WO + j * 8192, &tmWo, c * 64, h * DH + j * 64, BAR(B_WFULL));
      }
      for (int n = 0; n < 5; n++) {
        mbar_expect(BAR(B_RFULL + n), 16384);
        for (int j = 0; j < 4; j++) tma2d(sb + OFF_RING + n * 16384 + j * 4096, (n & 1) ? &tmWv : &tmWk, h * DH + j * 64, (((n >> 1) + ROT * c) % 14) * 32, BAR(B_RFULL + n));
      }
    }
    __syncwarp();
  }
  asm volatile("barrier.cluster.arrive.relaxed.aligned;" ::: "memory");

  if (warp < 8) {
    asm volatile("setmaxnreg.inc.sync.aligned.u32 160;");
    const int w = warp & 3, wg = warp >> 2;
    uint32_t wr[112];
    mbar_wait(BAR(B_WFULL), 0, 100);
    if (tid == 0) PROFP(3);
#pragma unroll
    for (int i = 0; i < 112; i++) wr[i] = 0;
    {
      int sl = wg, ph = 0, ch = ROT * c;
#pragma unroll 1
      for (int it = 0; it < 14; it++) {
        float d[16];
        const uint32_t dr = desc_lo(OFF_RING) + sl * 1024;
        mbar_wait(BAR(B_RFULL + sl), ph, 101);
        if (wg == 0) {
          wg_fence();
#pragma unroll
          for (int kk = 0; kk < 16; kk++)
            wgmma_ss_n32<0>(d, mkdesc(desc_lo(OFF_WQ + (kk >> 2) * 8192 + (kk & 3) * 32)), mkdesc(dr + (kk >> 2) * 256 + (kk & 3) * 2), kk > 0);
          wg_commit(); wg_wait0();
        } else {
          wg_fence();
#pragma unroll
          for (int kk = 0; kk < 16; kk++)
            wgmma_ss_n32<1>(d, mkdesc(desc_lo(OFF_WO + kk * 2048)), mkdesc(dr + (kk >> 2) * 256 + (kk & 3) * 2), kk > 0);
          wg_commit(); wg_wait0();
        }
        mbar_arrive_if(lane == 0, BAR(B_REMPTY + sl));
#define PK(k) do { _Pragma("unroll") for (int i = 0; i < 8; i++) wr[(k) * 8 + i] = pack_bf2(d[2 * i], d[2 * i + 1]); } while (0)
        switch (ch) {
        case 0: PK(0); break;
        case 1: PK(1); break;
        case 2: PK(2); break;
        case 3: PK(3); break;
        case 4: PK(4); break;
        case 5: PK(5); break;
        case 6: PK(6); break;
        case 7: PK(7); break;
        case 8: PK(8); break;
        case 9: PK(9); break;
        case 10: PK(10); break;
        case 11: PK(11); break;
        case 12: PK(12); break;
        default: PK(13); break;
        }
        if (tid == 0) PROFP(4 + it);
        if (++ch == 14) ch = 0;
        sl += 2;
        if (sl >= 5) { sl -= 5; ph ^= 1; }
      }
    }
    bar_sync(NB_PA, 256);
    if (tid == 0) PROFP(20);
    if (wg == 0) {
      const int i = lane >> 3, r = lane & 7;
      const uint32_t a = SBL + OFF_AC + ((i >> 1) * 8 + r) * 128 + (((2 * w + (i & 1)) ^ r) << 4);
#pragma unroll
      for (int kk = 0; kk < 28; kk++) stsm4t(a + kk * 2048, wr[4 * kk], wr[4 * kk + 1], wr[4 * kk + 2], wr[4 * kk + 3]);
    }
    asm volatile("barrier.cluster.wait.acquire.aligned;" ::: "memory");
    bar_sync(NB_START, NTHR);
    uint32_t pmask; asm volatile("ld.shared.b32 %0, [%1];" : "=r"(pmask) : "r"(s_mask) : "memory");
    pmask = __reduce_min_sync(0xffffffffu, pmask);
    if (tid == 0) PROFP(21);
    const uint32_t pg = (8 + h * 6 + (w >> 1)) * 8192 + (w & 1) * 2048;
    const uint32_t pg0 = pg + ((pmask >> (4 + (w >> 1))) & 1) * 4096, pg1 = pg + 3 * 8192 + ((pmask >> (7 + (w >> 1))) & 1) * 4096;
    uint32_t ra, rb, l8 = lane * 8;
    if (wg == 0) {
      ra = SBL + OFF_K + (lane & 7) * 128 + ((((lane >> 3) & 1) + 2 * w) ^ (lane & 7)) * 16 + (lane >> 4) * 1024;
      rb = SBL + OFF_K + w * 1024 + (lane & 7) * 128 + (((((lane >> 3) & 1) * 2 + (lane >> 4)) ^ (lane & 7)) << 4);
    } else {
      ra = SBL + OFF_Z + (16 * w + (lane >> 4) * 8 + (lane & 7)) * 80 + ((lane >> 3) & 1) * 32;
      rb = mapa(sb + OFF_RS + h * 128 + (g & 1) * 64 + t * 16, 4 * w + (g >> 1));
    }
    PROF_INIT(w == 0);
    PIN(ra); PIN(rb); PIN(l8);
    int zi = 0, zph = 1;
#pragma unroll 1
    for (int u = 0; u <= NSEG; u++) {
      const int P = u & 1;
      if (u < XLIM) mbar_wait(BAR(B_XFULL + P), (u >> 1) & 1, 102);
      if (wg == 0) {
        if (u >= 4) mbar_wait(BAR(B_KEMPTY + (u & 3)), ((u - 4) >> 2) & 1, 103);
        OPQ(l8);
        const uint32_t cpy = w * 512 + l8 * 2;
        const uint32_t xs = SBL + OFF_XS + P * XSLOT + c * 5120 + cpy, kd = SBL + OFF_K + (u & 3) * KSLOT + 5120 + cpy;
        float4 a = lds128f(xs), b = lds128f(xs + 2048);
        sts128f(kd, a); sts128f(kd + 2048, b);
      }
      float d[20];
      const uint32_t dxs = desc_lo(OFF_XS) + P * (XSLOT >> 4);
      if (u > 0) bar_sync(wg ? NB_MREADY : NB_GO, 256);
      wg_fence();
#pragma unroll
      for (int kk = 0; kk < 28; kk++) {
        wgmma_rs_n40(d, &wr[4 * kk], mkdesc(dxs + (((kk >> 2) * 5120 + (kk & 3) * 32) >> 4)), kk > 0);
        if (kk == 0) { PROFS(wg ? 11 : 0, u & 63); }
      }
      wg_commit();
      mbar_arrive_if(wg && l8 == 0, BAR(B_WDONE + P));
      if (wg && u >= 6) mbar_wait(BAR(B_ZEMPTY + zi), zph, 203);
      wg_wait0();
      uint32_t pk[10];
#pragma unroll
      for (int i = 0; i < 10; i++) pk[i] = pack_bf2(d[2 * i], d[2 * i + 1]);
      OPQ(ra); OPQ(rb); OPQ(l8);
      if (wg == 0) {
        const uint32_t ko = (u & 3) * KSLOT;
        stsm4t(ra + ko, pk[0], pk[1], pk[2], pk[3]); stsm4t(ra + ko + 2048, pk[4], pk[5], pk[6], pk[7]); stsm2t(ra + ko + 4096, pk[8], pk[9]);
        bar_sync(NB_W0, 128);
        PROF(1, u & 63);
        if (u < NSEG - 1) {
          uint32_t b[8];
          ldsm4(b[0], b[1], b[2], b[3], rb + ko);
          ldsm4(b[4], b[5], b[6], b[7], (rb + ko) ^ 64);
          mbar_wait(BAR(B_AG + P), (u >> 1) & 1, 104);
          const uint32_t ms = l8 + SBL + OFF_AG + P * 1024;
          const uint2 m0 = lds64(ms), m1 = lds64(ms + 256), m2 = lds64(ms + 512), m3 = lds64(ms + 768);
          float e0[4] = {0, 0, 0, 0}, e1[4] = {0, 0, 0, 0}, e2[4] = {0, 0, 0, 0}, e3[4] = {0, 0, 0, 0};
          mma16(e0, m0.x, m0.y, m1.x, m1.y, b[0], b[1]); mma16(e1, m0.x, m0.y, m1.x, m1.y, b[2], b[3]);
          mma16(e2, m2.x, m2.y, m3.x, m3.y, b[4], b[5]); mma16(e3, m2.x, m2.y, m3.x, m3.y, b[6], b[7]);
          const uint32_t v0 = (__float_as_uint((e0[0] + e1[2]) + (e2[0] + e3[2])) & ~1u) | tag_of(u), v1 = __float_as_uint((e0[1] + e1[3]) + (e2[1] + e3[3]));
          unsigned char* pw = g_pool + (pg + c * 256 + P * 3 * 8192 + l8);
          st_rlx2(pw, v0, v1); st_rlx2(pw + 4096, v0, v1);
          PROF(10, u & 63);
        }
        mbar_arrive_if(l8 == 0, BAR(B_KFULL + (u & 3)));
        mbar_arrive_rem_if(l8 == 0 && u + 2 < NSEG, mapa(BAR(B_XEMPTY), (u + 2) & 15));
        if (u < NSEG - 1) {
          uint2 v[7];
          const uint32_t po = delay_clk<W0_DELAY>((P ? pg1 : pg0) + l8, never);
          poll_issue(v, po);
          PROFV(14, u & 63, poll_finish(v, po, tag_of(u) - 1));
          sts64f(l8 + SBL + OFF_SMX + w * 256, sum7x(v), sum7y(v));
          bar_arrive(NB_EX, 256);
          PROF(2, u & 63);
        }
      } else {
        const uint32_t zo = zi * ZSLOT;
        stsm4(ra + zo, pk[0], pk[4], pk[1], pk[5]); stsm4(ra + zo + 16, pk[2], pk[6], pk[3], pk[7]);
        if (u > 0 && u < NSEG) {
          const uint32_t zp = ra + (zi ? zi - 1 : 5) * ZSLOT;
          uint32_t b[8];
          ldsm4(b[0], b[1], b[2], b[3], zp);
          ldsm4(b[4], b[5], b[6], b[7], zp + 16);
          float2 r[5];
          bar_sync(NB_EX, 256);
#pragma unroll
          for (int i = 0; i < 4; i++) r[i] = lds64f(l8 + SBL + OFF_SMX + i * 256);
          float M = fmaxf(fmaxf(fmaxf(r[0].x, r[0].y), fmaxf(r[1].x, r[1].y)), fmaxf(fmaxf(r[2].x, r[2].y), fmaxf(r[3].x, r[3].y)));
          const uint32_t rsa = rb + (P ^ 1) * 2048, rsb = (rb & 0xFF000000u) | (SB + OFF_BAR + B_RS * 8 + (P ^ 1) * 8);
          bar_sync(NB_SM, 160);
          r[4] = lds64f(l8 + SBL + OFF_SMX + 1024);
          M = fmaxf(M, fmaxf(r[4].x, r[4].y));
          PROF(5, u & 63);
          M = fmaxf(M, __shfl_xor_sync(0xffffffffu, M, 1));
          M = fmaxf(M, __shfl_xor_sync(0xffffffffu, M, 2));
          const float mc = -M * C2;
          uint32_t pe[5];
#pragma unroll
          for (int i = 0; i < 5; i++) { r[i].x = ex2(fmaf(r[i].x, C2, mc)); r[i].y = ex2(fmaf(r[i].y, C2, mc)); pe[i] = pack_bf2(r[i].x, r[i].y); }
          float oa0[4] = {0, 0, 0, 0}, oa1[4] = {0, 0, 0, 0}, ob0[4] = {0, 0, 0, 0}, ob1[4] = {0, 0, 0, 0};
          float den = ((r[0].x + r[0].y) + (r[1].x + r[1].y)) + ((r[2].x + r[2].y) + (r[3].x + r[3].y)) + (r[4].x + r[4].y);
          float den2 = __shfl_xor_sync(0xffffffffu, den, 1);
          mma16(oa0, pe[0], pe[1], pe[2], pe[3], b[0], b[1]); mma16(oa1, pe[0], pe[1], pe[2], pe[3], b[2], b[3]);
          mma16(ob0, pe[0], pe[1], pe[2], pe[3], b[4], b[5]); mma16(ob1, pe[0], pe[1], pe[2], pe[3], b[6], b[7]);
          float om0[4] = {0, 0, 0, 0}, om1[4] = {0, 0, 0, 0};
          mma8(om0, pe[3], pe[4], pk[8]); mma8(om1, pe[3], pe[4], pk[9]);
          den += den2;
          den += __shfl_xor_sync(0xffffffffu, den, 2);
          const float rd = rcpf(den);
          st_async4(rsa, (oa0[0] + ob0[2] + om0[2]) * rd, (oa0[1] + ob0[3] + om0[3]) * rd, (oa1[0] + ob1[2] + om1[2]) * rd, (oa1[1] + ob1[3] + om1[3]) * rd, rsb);
        }
        if (u > 0) bar_arrive(NB_GO, 256);
        PROF(12, u & 63);
        stsm1(ra + zo + 64, pk[8]); stsm1(ra + zo + 64 + 640, pk[9]);
        __syncwarp();
        mbar_arrive_if(l8 == 0, BAR(B_ZFULL + zi));
        mbar_arrive_rem_if(l8 == 0 && u + 2 < NSEG, mapa(BAR(B_XEMPTY), (u + 2) & 15));
        if (++zi == 6) { zi = 0; zph ^= 1; }
      }
    }
    role_exit(s_done, lane, false);
  } else if (warp < 12) {
    asm volatile("setmaxnreg.dec.sync.aligned.u32 112;");
    if (warp == 11) {
      if (lane == 0) {
        for (int n = 5; n < 28; n++) {
          const int sl = n % 5;
          mbar_wait(BAR(B_REMPTY + sl), ((n - 5) / 5) & 1, 300);
          mbar_expect(BAR(B_RFULL + sl), 16384);
          for (int j = 0; j < 4; j++) tma2d(sb + OFF_RING + sl * 16384 + j * 4096, (n & 1) ? &tmWv : &tmWk, h * DH + j * 64, (((n >> 1) + ROT * c) % 14) * 32, BAR(B_RFULL + sl));
        }
      }
      __syncwarp();
    } else if (warp == 10) {
      helper_prologue(0, lane, xin);
    if (warp == 10 && lane == 0) {
      PROFP(22);
      fence_gpu();
      const uint32_t old = atom_add(&g_gridbar, 1);
      const uint32_t target = (old / NCTA + 1) * NCTA;
      long long t0 = clock64();
      while ((int)(ld_acq(&g_gridbar) - target) < 0) { if (clock64() - t0 > TIMEOUT) fail(304); }
      PROFP(23);
      fence_proxy_all();
      if (h < 2) for (int j = 0; j < 7; j++) tma2d_mc(sb + OFF_XS + h * XSLOT + j * 5120, &tmX, j * 64, h * 32, BAR(B_XFULL + h), 0xFFFF);
    }
      __syncwarp();
    } else {
      bar_sync(NB_HELP, 224);
      probe_pages(warp - 4, lane, h, c, s_mask);
    }
    asm volatile("barrier.cluster.wait.acquire.aligned;" ::: "memory");
    bar_sync(NB_START, NTHR);
    uint32_t pmask; asm volatile("ld.shared.b32 %0, [%1];" : "=r"(pmask) : "r"(s_mask) : "memory");
      pmask = __reduce_min_sync(0xffffffffu, pmask);
    const int w = warp - 8;
    const uint32_t r7 = lane & 7, ch = lane >> 3;
    uint32_t ab0 = SBL + OFF_AC + (16 * w + (ch & 1) * 8 + r7) * 128 + (((ch >> 1) ^ r7) << 4);
    uint32_t mst = SBL + OFF_XS + XSLOT + 4096 + (ch >> 1) * 5120 + r7 * 128 + (((2 * w + (ch & 1)) ^ r7) << 4);
    uint32_t l8 = SBL + lane * 8;
    const uint32_t pg = (2 * (w >> 1) + (c & 1)) * 8192 + (w & 1) * 2048 + lane * 8;
    uint32_t prd = pg + ((pmask >> (w >> 1)) & 1) * 4096;
    const int prx = 4 * 8192 + (int)(((pmask >> (2 + (w >> 1))) & 1) - ((pmask >> (w >> 1)) & 1)) * 4096;
    uint32_t psm = (8 + h * 6 + 2) * 8192 + (w & 1) * 4096 + c * 256 + lane * 8;
    const uint32_t ps0 = (8 + h * 6 + 2) * 8192 + ((pmask >> 6) & 1) * 4096, ps1 = (8 + h * 6 + 5) * 8192 + ((pmask >> 9) & 1) * 4096;
    const uint32_t wq = h >> 2;
    const uint32_t r8 = (lane >> 1) & 7, rg = (lane & 1) + (lane >> 4) * 2;
    uint32_t pub = (2 * (wq >> 1) + (rg >> 1)) * 8192 + (rg & 1) * 4096 + (wq & 1) * 2048 + c * 256 + (h & 3) * 64 + r8 * 8;
    uint32_t aga = mapa(sb + OFF_AG + wq * 256 + (h & 3) * 64 + r8 * 8, rg * 4), agb = mapa(BAR(B_AG), rg * 4);
    const uint32_t rstep = mapa(sb, 1) - mapa(sb, 0);
    uint32_t rsl = SBL + OFF_RS + 2048 + (lane >> 4) * 1024 + (lane & 15) * 8;
    PROF_INIT(w == TPW);
    PIN(ab0); PIN(mst); PIN(l8); PIN(prd); PIN(psm); PIN(pub); PIN(aga); PIN(agb); PIN(rsl);
    auto step = [&](auto first_, auto last_, const int s) {
      constexpr bool FIRST = decltype(first_)::value, LAST = decltype(last_)::value;
      if (w == 0) {
        uint32_t w0, w1;
        if (FIRST) {
          const uint32_t* mp = (const uint32_t*)(mem0 + (2 * (h & 3) + (r8 >> 2)) * DM + c * 64 + wq * 16 + (r8 & 3) * 2);
          w0 = __ldg(mp); w1 = __ldg(mp + 4);
          st_rlx2(g_pool + pub, 1, 0);
        } else {
          const uint32_t tg = tag_of(s);
          mbar_wait(BAR(B_RS + ((s - 1) & 1)), ((s - 1) >> 1) & 1, 600);
          PROF(4, s);
          float2 v[8];
#pragma unroll
          for (int j = 0; j < 8; j++) v[j] = lds64f(rsl + j * 128);
          float x = ((v[0].x + v[1].x) + (v[2].x + v[3].x)) + ((v[4].x + v[5].x) + (v[6].x + v[7].x)), y = ((v[0].y + v[1].y) + (v[2].y + v[3].y)) + ((v[4].y + v[5].y) + (v[6].y + v[7].y));
          x += __shfl_xor_sync(0xffffffffu, x, 16); y += __shfl_xor_sync(0xffffffffu, y, 16);
          const uint32_t mine = pack_bf2(x, y), other = __shfl_xor_sync(0xffffffffu, mine, 1);
          const bool odd = rsl & 8;
          w0 = ((odd ? other : mine) & ~1u) | tg;
          w1 = odd ? mine : other;
          st_rlx2(g_pool + pub, w0, w1);
          __syncwarp();
        }
        if (!LAST) {
#pragma unroll
          for (int j = 0; j < 4; j++) st_async2(aga + j * rstep, w0, w1, agb + j * rstep);
        }
        PROF(21, s);
        if (!FIRST) mbar_expect_if(lane == 0 && s + 1 < NSEG - 1, BAR(B_RS + ((s - 1) & 1)), 2048);
        pub ^= 32768; aga += (s & 1) ? -1024 : 1024; agb += (s & 1) ? -8 : 8; rsl += (s & 1) ? 2048 : -2048;
      }
      uint32_t ta[16];
      uint2 v[7];
      if (!LAST) {
        uint32_t a[2][7][4];
#pragma unroll
        for (int ks = 0; ks < 2; ks++)
#pragma unroll
          for (int mt = 0; mt < 7; mt++) ldsm4(a[ks][mt][0], a[ks][mt][1], a[ks][mt][2], a[ks][mt][3], (ab0 ^ (ks << 5)) + mt * 8192);
        mbar_wait(BAR(B_AG + (s & 1)), (s >> 1) & 1, 400);
        const uint32_t ms = l8 + OFF_AG + (s & 1) * 1024;
        uint2 b[4];
#pragma unroll
        for (int ks = 0; ks < 4; ks++) b[ks] = lds64(ms + ks * 256);
        PROF(6, s);
        if (TPOLL_AT < 0 && !FIRST) { poll_issue(v, prd); __syncwarp(); }
        float acc[7][4];
#pragma unroll
        for (int ks = 0; ks < 4; ks++) {
#pragma unroll
          for (int mt = 0; mt < 7; mt++) {
            uint32_t(&am)[4] = a[ks & 1][mt];
            if (ks == 0) acc[mt][0] = acc[mt][1] = acc[mt][2] = acc[mt][3] = 0;
            mma16(acc[mt], am[0], am[1], am[2], am[3], b[ks].x, b[ks].y);
            if (ks == 1 || ks == 2) { uint32_t(&an)[4] = a[(ks + 1) & 1][mt]; ldsm4(an[0], an[1], an[2], an[3], (ab0 ^ ((ks + 1) << 5)) + mt * 8192); }
          }
          if (ks == TPOLL_AT && !FIRST) { __syncwarp(); poll_issue(v, prd); }
          __syncwarp();
        }
#pragma unroll
        for (int mt = 0; mt < 7; mt++) {
          ta[2 * mt] = movm(pack_bf2(acc[mt][0], acc[mt][1]));
          ta[2 * mt + 1] = movm(pack_bf2(acc[mt][2], acc[mt][3]));
        }
        ta[14] = __float_as_uint(acc[6][1]); ta[15] = __float_as_uint(acc[6][3]);
        PROF(20, s);
      } else {
        poll_issue(v, prd);
      }
      if (FIRST) {
        const uint32_t* mp = (const uint32_t*)(mem0 + g * DM + 16 * w + 2 * t);
#pragma unroll
        for (int mt = 0; mt < 7; mt++) { v[mt].x = __ldg(mp + mt * 32); v[mt].y = __ldg(mp + mt * 32 + 4); }
      } else {
        PROFV(16, s, poll_finish(v, prd, tag_of(s) - 1));
      }
      PROF(7, s);
      float e[7][4] = {};
      if (!LAST) {
        mma16(e[0], ta[0], ta[2], ta[1], ta[3], v[0].x, v[0].y); mma16(e[1], ta[0], ta[2], ta[1], ta[3], v[1].x, v[1].y);
        mma16(e[2], ta[4], ta[6], ta[5], ta[7], v[2].x, v[2].y); mma16(e[3], ta[4], ta[6], ta[5], ta[7], v[3].x, v[3].y);
        mma16(e[4], ta[8], ta[10], ta[9], ta[11], v[4].x, v[4].y); mma16(e[5], ta[8], ta[10], ta[9], ta[11], v[5].x, v[5].y);
        mma16(e[6], ta[12], ta[14], ta[13], ta[15], v[6].x, v[6].y);
      }
      stsm4(mst, v[0].x, v[0].y, v[1].x, v[1].y); stsm4(mst + 10240, v[2].x, v[2].y, v[3].x, v[3].y);
      stsm4(mst + 20480, v[4].x, v[4].y, v[5].x, v[5].y); stsm2(mst + 30720, v[6].x, v[6].y);
      if (!LAST) {
        sts64f(l8 + OFF_SMM + w * 256, ((e[0][0] + e[1][2]) + (e[2][0] + e[3][2])) + ((e[4][0] + e[5][2]) + e[6][0]), ((e[0][1] + e[1][3]) + (e[2][1] + e[3][3])) + ((e[4][1] + e[5][3]) + e[6][1]));
        if (w < 2) {
          bar_sync(NB_T, 128);
          const float2 a = lds64f(l8 + OFF_SMM), b = lds64f(l8 + OFF_SMM + 256), cc = lds64f(l8 + OFF_SMM + 512), dd = lds64f(l8 + OFF_SMM + 768);
          st_rlx2(g_pool + psm, (__float_as_uint((a.x + b.x) + (cc.x + dd.x)) & ~1u) | tag_of(s), __float_as_uint((a.y + b.y) + (cc.y + dd.y)));
        } else {
          bar_arrive(NB_T, 128);
        }
        PROF(22, s);
      }
      fence_proxy_smem();
      bar_arrive(NB_MREADY, 256);
      PROF(15, s);
      if (!LAST && w == 2) {
        const uint32_t po = delay_clk<T_DELAY>(((s & 1) ? ps1 : ps0) + l8 - SBL, never);
        PROF(4, s);
        poll_issue(v, po);
        PROFV(17, s, poll_finish(v, po, tag_of(s) - 1));
        sts64f(l8 + OFF_SMX + 1024, sum7x(v), sum7y(v));
        bar_arrive(NB_SM, 160);
        PROF(9, s);
      }
      mst += (s & 1) ? XSLOT : -XSLOT; prd += (s & 1) ? -prx : prx; psm += (s & 1) ? -3 * 8192 : 3 * 8192;
      if (w == 3) mbar_expect_if(lane == 0 && s + 2 < NSEG - 1, BAR(B_AG + (s & 1)), 1024);
    };
    step(True_(), False_(), 0);
#pragma unroll 1
    for (int s = 1; s < NSEG - 1; s++) step(False_(), False_(), s);
    step(False_(), True_(), NSEG - 1);
    role_exit(s_done, lane, false);
  } else {
    asm volatile("setmaxnreg.dec.sync.aligned.u32 80;");
    helper_prologue(warp - 11, lane, xin);
    probe_pages(warp - 12, lane, h, c, s_mask);
    if (tid == 384) PROFP(1);
    asm volatile("barrier.cluster.wait.acquire.aligned;" ::: "memory");
    bar_sync(NB_START, NTHR);
    const int par = (warp >> 1) & 1;
    {
      const int IT = warp & 1;
      constexpr int NX = 4;
      const uint32_t r7 = lane & 7, ch = lane >> 3;
      uint32_t ka = SBL + OFF_K + 5120 + (16 * IT + (ch & 1) * 8 + r7) * 128 + (((ch >> 1) ^ r7) << 4);
      uint32_t kb = SBL + OFF_K + r7 * 128 + ((ch ^ r7) << 4);
      uint32_t oa = mapa(sb + OFF_OUT + (tid & 64) * 128 + h * 512 + (lane & 7) * 16, 8 * IT + (lane >> 3));
      uint32_t l16 = lane * 16;
      PROF_INIT(IT == XPW);
      PIN(ka); PIN(kb); PIN(oa); PIN(l16);
      auto out_reduce = [&](const int sp) {
        mbar_wait(BAR(B_OUTF + par), (sp >> 1) & 1, 700);
        OPQ(l16);
        float4 a = make_float4(0, 0, 0, 0);
#pragma unroll 1
        for (int j0 = 0; j0 < 16; j0 += 4) {
          float4 v[4];
#pragma unroll
          for (int j = 0; j < 4; j++) v[j] = lds128f(SBL + OFF_OUT + par * 8192 + (j0 + j) * 512 + l16);
          a.x += (v[0].x + v[1].x) + (v[2].x + v[3].x); a.y += (v[0].y + v[1].y) + (v[2].y + v[3].y);
          a.z += (v[0].z + v[1].z) + (v[2].z + v[3].z); a.w += (v[0].w + v[1].w) + (v[2].w + v[3].w);
          __syncwarp();
        }
        mbar_expect_if(l16 == 0 && sp + 2 < NSEG, BAR(B_OUTF + par), 8192);
        __syncwarp();
        mbar_arrive_rem_if(l16 < 256 && sp + 2 < NSEG, mapa(BAR(B_OUTC + par), l16 >> 4));
        uint32_t* dst = (uint32_t*)((unsigned char*)g_s + ((size_t)(sp * 32 + 2 * h) * DM + c * 64) * 2 + ((l16 >> 6) & 1) * (DM * 2) + ((l16 >> 2) & 96) + ((l16 >> 2) & 12));
        dst[0] = pack_bf2(a.x, a.y); dst[4] = pack_bf2(a.z, a.w);
      };
      auto xload = [&](const int u) {
        mbar_wait(BAR(B_XFULL + (u & 1)), ((u - 2) >> 1) & 1, 301);
        mbar_expect_if(l16 == 0, BAR(B_XFULL + (u & 1)), 28672);
        if ((u & 15) == (int)h) {
          mbar_wait(BAR(B_XEMPTY), (h < 2 ? (u >> 4) - 1 : (u >> 4)) & 1, 302);
#pragma unroll 1
          for (int j = 0; j < 7; j++) {
            if (l16 == 0) tma2d_mc(sb + OFF_XS + (u & 1) * XSLOT + j * 5120, &tmX, j * 64, u * 32, BAR(B_XFULL + (u & 1)), 0xFFFF);
            __syncwarp();
            l16 = delay_clk<TMA_DT>(l16, never);
          }
        }
      };
      mbar_wait(BAR(B_WDONE + par), 0, 500);
      if (IT == 0 && par == 1 && 2 < XLIM) xload(2);
      int z2 = par + 2, zq = 0;
      uint32_t p[NX + 1][2] = {};
#pragma unroll 1
      for (int s = par; s < NSEG + 2; s += 2) {
        PROF(23, s & 63);
        if (s < NSEG) mbar_wait(BAR(B_KFULL + ((s + 1) & 3)), ((s + 1) >> 2) & 1, 501);
        if (IT == 0 && s + 3 < XLIM) xload(s + 3);
        {
          if (s >= 4) mbar_wait(BAR(B_OUTC + par), ((s - 4) >> 1) & 1, 505);
          const int z0 = z2 >= 4 ? z2 - 4 : z2 + 2, z1 = z2 >= 3 ? z2 - 3 : z2 + 3;
          OPQ(oa); OPQ(l16);
          const uint32_t zb = SBL + OFF_Z + ((l16 >> 4) & 7) * 80 + (l16 >> 7) * 16;
          const uint32_t zx = zb + z0 * ZSLOT, zm = zb + z1 * ZSLOT + 64 + (l16 >> 7) * (640 - 16);
          const uint32_t ob = (oa & 0xFF000000u) | (SB + OFF_BAR + B_OUTF * 8) | (par * 8);
          uint32_t wm[4], b[4][4];
          ldsm4(wm[0], wm[1], wm[2], wm[3], zm);
#pragma unroll
          for (int fn = 0; fn < 4; fn++) ldsm4(b[fn][0], b[fn][1], b[fn][2], b[fn][3], zx + fn * 640);
          if (s + 2 <= NSEG) mbar_wait(BAR(B_WDONE + par), ((s + 2) >> 1) & 1, 502);
          PROF(13, s & 63);
          if (s >= 2) {
#pragma unroll 1
            for (int hf = 0; hf < 2; hf++) {
              float o[4][4] = {};
#pragma unroll
              for (int fn = 0; fn < 4; fn++) mma8(o[fn], p[0][0], p[0][1], wm[fn]);
#pragma unroll
              for (int fn = 0; fn < 4; fn++) mma16(o[fn], p[1][0], p[1][1], p[2][0], p[2][1], b[fn][0], b[fn][1]);
#pragma unroll
              for (int fn = 0; fn < 4; fn++) mma16(o[fn], p[3][0], p[3][1], p[4][0], p[4][1], b[fn][2], b[fn][3]);
              __syncwarp();
              ldsm4(wm[0], wm[1], wm[2], wm[3], zm + 2560);
#pragma unroll
              for (int fn = 0; fn < 4; fn++) ldsm4(b[fn][0], b[fn][1], b[fn][2], b[fn][3], zx + 2560 + fn * 640);
#pragma unroll
              for (int q = 0; q < 2; q++) {
                st_async4(oa + (2 * hf + q) * 128, o[2 * q][0], o[2 * q][1], o[2 * q + 1][0], o[2 * q + 1][1], ob);
                st_async4(oa + (4u << 24) + (2 * hf + q) * 128, o[2 * q][2], o[2 * q][3], o[2 * q + 1][2], o[2 * q + 1][3], ob + (4u << 24));
              }
            }
            __syncwarp();
            mbar_arrive_if(l16 < 32, BAR(B_ZEMPTY + (l16 ? z1 : z0)));
          }
        }
        PROF(19, s & 63);
        float ret[NX + 1] = {};
        unsigned char* acc = (unsigned char*)g_sacc + (((s & 63) * NH + h) * 8 + IT * 3) * 512 + l16;
        if (s < NSEG) {
        OPQ(ka); OPQ(kb); OPQ(l16);
        const uint32_t kx = (s & 3) * KSLOT, km = ((s + 1) & 3) * KSLOT + 4096;
        float sc[NX + 1][4];
#pragma unroll
        for (int i = 0; i <= NX; i++) { sc[i][0] = sc[i][1] = sc[i][2] = sc[i][3] = 0; }
#pragma unroll 1
        for (int q = 0; q < 2; q++) {
          uint32_t a0[4], a1[4];
          ldsm4(a0[0], a0[1], a0[2], a0[3], (ka ^ (q << 6)) + kx);
          ldsm4(a1[0], a1[1], a1[2], a1[3], (ka ^ (q << 6) ^ 32) + kx);
#pragma unroll
          for (int nt = 0; nt <= NX; nt++) {
            uint32_t b0, b1, b2, b3;
            ldsm4(b0, b1, b2, b3, (kb ^ (q << 6)) + (nt == 0 ? km : kx + (nt - 1) * 1024));
            mma16(sc[nt], a0[0], a0[1], a0[2], a0[3], b0, b1);
            mma16(sc[nt], a1[0], a1[1], a1[2], a1[3], b2, b3);
          }
          __syncwarp();
        }
        OPQ(l16);
        mbar_arrive_if(l16 < 32, BAR(B_KEMPTY + ((s + (l16 >> 4)) & 3)));
        PROF(3, s);
        if (s + 2 <= NSEG) mbar_wait(BAR(B_ZFULL + z2), zq, 504);
        else mbar_wait(BAR(B_ZFULL + NSEG % 6), (NSEG / 6) & 1, 504);
        PROF(18, s);
#pragma unroll
        for (int i = 0; i <= NX; i++) {
          if (i < 3 || IT) ret[i] = atom_add4(acc + i * 512, sc[i][0], sc[i][1], sc[i][2], sc[i][3]);
        }
        __syncwarp();
        }
        if (IT == 0 && s >= 2) out_reduce(s - 2);
        if (s >= NSEG) break;
        z2 += 2;
        if (z2 >= 6) { z2 -= 6; zq ^= 1; }
        float sc[NX + 1][4] = {};
        const float rsum = (ret[0] + ret[1] + ret[2]) + (ret[3] + ret[4]);
        const uint32_t one = __any_sync(0xffffffffu, __float_as_uint(rsum) == 0x7fc01234u) ? 0x101u : 1u;
        uint32_t* cnt = g_scnt + (s * NH + h) * 2 + IT;
        asm volatile("{.reg .pred p; setp.eq.u32 p, %2, 0; @p red.relaxed.gpu.global.add.u32 [%0], %1;}" ::"l"(cnt), "r"(one), "r"(l16) : "memory");
        asm volatile("{\n.reg .pred p;\n.reg .b32 v, n;\nmov.u32 n, 0;\n"
                     "C_LOOP:\nld.relaxed.gpu.global.u32 v, [%0];\nand.b32 v, v, 255;\nsetp.ge.u32 p, v, 7;\nvote.sync.all.pred p, p, 0xffffffff;\n@p bra.uni C_DONE;\n"
                     "add.u32 n, n, 1;\nsetp.lt.u32 p, n, 0x400000;\n@p bra.uni C_LOOP;\ntrap;\nC_DONE:\n}\n" ::"l"(cnt) : "memory");
#pragma unroll
        for (int i = 0; i <= NX; i++) if (i < 3 || IT) { float4 v = ld_rlx4f(acc + i * 512); sc[i][0] = v.x; sc[i][1] = v.y; sc[i][2] = v.z; sc[i][3] = v.w; }
        OPQ(l16);
        const int dj = (int)(l16 >> 6) - (int)((l16 >> 3) & 6) + 16 * IT;
#pragma unroll
        for (int nt = 0; nt < 4; nt++) {
          if (dj < 8 * nt) sc[1 + nt][0] = -INFINITY;
          if (dj < 8 * nt + 1) sc[1 + nt][1] = -INFINITY;
          if (nt > 0 && dj < 8 * nt - 8) sc[1 + nt][2] = -INFINITY;
          if (nt > 0 && dj < 8 * nt - 7) sc[1 + nt][3] = -INFINITY;
        }
        float m0 = fmaxf(sc[0][0], sc[0][1]), m1 = fmaxf(sc[0][2], sc[0][3]);
#pragma unroll
        for (int i = 1; i <= NX; i++) { m0 = fmaxf(m0, fmaxf(sc[i][0], sc[i][1])); m1 = fmaxf(m1, fmaxf(sc[i][2], sc[i][3])); }
        m0 = fmaxf(m0, __shfl_xor_sync(0xffffffffu, m0, 1)); m1 = fmaxf(m1, __shfl_xor_sync(0xffffffffu, m1, 1));
        m0 = fmaxf(m0, __shfl_xor_sync(0xffffffffu, m0, 2)); m1 = fmaxf(m1, __shfl_xor_sync(0xffffffffu, m1, 2));
        m0 *= -C2; m1 *= -C2;
        float d0 = 0, d1 = 0;
#pragma unroll
        for (int i = 0; i <= NX; i++) {
          sc[i][0] = ex2(fmaf(sc[i][0], C2, m0)); sc[i][1] = ex2(fmaf(sc[i][1], C2, m0)); sc[i][2] = ex2(fmaf(sc[i][2], C2, m1)); sc[i][3] = ex2(fmaf(sc[i][3], C2, m1));
          d0 += sc[i][0] + sc[i][1]; d1 += sc[i][2] + sc[i][3];
        }
        d0 += __shfl_xor_sync(0xffffffffu, d0, 1); d1 += __shfl_xor_sync(0xffffffffu, d1, 1);
        d0 += __shfl_xor_sync(0xffffffffu, d0, 2); d1 += __shfl_xor_sync(0xffffffffu, d1, 2);
        d0 = rcpf(d0); d1 = rcpf(d1);
#pragma unroll
        for (int i = 0; i <= NX; i++) { p[i][0] = pack_bf2(sc[i][0] * d0, sc[i][1] * d0); p[i][1] = pack_bf2(sc[i][2] * d1, sc[i][3] * d1); }
      }
    }
    if (lane == 0) PROFP(24 + (warp & 3));
    role_exit(s_done, lane, true);
    if (tid == 384) PROFP(28);
  }
}

DEVI void wgmma_n112(float (&d)[56], uint64_t da, uint64_t db, int sc) {
  asm volatile("{.reg .pred p; setp.ne.b32 p, %58, 0;\n"
               "wgmma.mma_async.sync.aligned.m64n112k16.f32.bf16.bf16 {%0,%1,%2,%3,%4,%5,%6,%7,%8,%9,%10,%11,%12,%13,%14,%15,%16,%17,%18,%19,%20,%21,%22,%23,%24,%25,%26,%27,%28,%29,%30,%31,%32,%33,%34,%35,%36,%37,%38,%39,%40,%41,%42,%43,%44,%45,%46,%47,%48,%49,%50,%51,%52,%53,%54,%55}, %56, %57, p, 1, 1, 1, 0;}\n"
               : "+f"(d[0]), "+f"(d[1]), "+f"(d[2]), "+f"(d[3]), "+f"(d[4]), "+f"(d[5]), "+f"(d[6]), "+f"(d[7]), "+f"(d[8]), "+f"(d[9]), "+f"(d[10]), "+f"(d[11]), "+f"(d[12]), "+f"(d[13]), "+f"(d[14]), "+f"(d[15]), "+f"(d[16]), "+f"(d[17]), "+f"(d[18]), "+f"(d[19]), "+f"(d[20]), "+f"(d[21]), "+f"(d[22]), "+f"(d[23]), "+f"(d[24]), "+f"(d[25]), "+f"(d[26]), "+f"(d[27]), "+f"(d[28]), "+f"(d[29]), "+f"(d[30]), "+f"(d[31]), "+f"(d[32]), "+f"(d[33]), "+f"(d[34]), "+f"(d[35]), "+f"(d[36]), "+f"(d[37]), "+f"(d[38]), "+f"(d[39]), "+f"(d[40]), "+f"(d[41]), "+f"(d[42]), "+f"(d[43]), "+f"(d[44]), "+f"(d[45]), "+f"(d[46]), "+f"(d[47]), "+f"(d[48]), "+f"(d[49]), "+f"(d[50]), "+f"(d[51]), "+f"(d[52]), "+f"(d[53]), "+f"(d[54]), "+f"(d[55])
               : "l"(da), "l"(db), "r"(sc));
}
DEVI void wgmma_n104(float (&d)[52], uint64_t da, uint64_t db, int sc) {
  asm volatile("{.reg .pred p; setp.ne.b32 p, %54, 0;\n"
               "wgmma.mma_async.sync.aligned.m64n104k16.f32.bf16.bf16 {%0,%1,%2,%3,%4,%5,%6,%7,%8,%9,%10,%11,%12,%13,%14,%15,%16,%17,%18,%19,%20,%21,%22,%23,%24,%25,%26,%27,%28,%29,%30,%31,%32,%33,%34,%35,%36,%37,%38,%39,%40,%41,%42,%43,%44,%45,%46,%47,%48,%49,%50,%51}, %52, %53, p, 1, 1, 1, 0;}\n"
               : "+f"(d[0]), "+f"(d[1]), "+f"(d[2]), "+f"(d[3]), "+f"(d[4]), "+f"(d[5]), "+f"(d[6]), "+f"(d[7]), "+f"(d[8]), "+f"(d[9]), "+f"(d[10]), "+f"(d[11]), "+f"(d[12]), "+f"(d[13]), "+f"(d[14]), "+f"(d[15]), "+f"(d[16]), "+f"(d[17]), "+f"(d[18]), "+f"(d[19]), "+f"(d[20]), "+f"(d[21]), "+f"(d[22]), "+f"(d[23]), "+f"(d[24]), "+f"(d[25]), "+f"(d[26]), "+f"(d[27]), "+f"(d[28]), "+f"(d[29]), "+f"(d[30]), "+f"(d[31]), "+f"(d[32]), "+f"(d[33]), "+f"(d[34]), "+f"(d[35]), "+f"(d[36]), "+f"(d[37]), "+f"(d[38]), "+f"(d[39]), "+f"(d[40]), "+f"(d[41]), "+f"(d[42]), "+f"(d[43]), "+f"(d[44]), "+f"(d[45]), "+f"(d[46]), "+f"(d[47]), "+f"(d[48]), "+f"(d[49]), "+f"(d[50]), "+f"(d[51])
               : "l"(da), "l"(db), "r"(sc));
}
DEVI void ldsm4t(uint32_t& r0, uint32_t& r1, uint32_t& r2, uint32_t& r3, uint32_t a) {
  asm volatile("ldmatrix.sync.aligned.m8n8.x4.trans.shared.b16 {%0,%1,%2,%3}, [%4];" : "=r"(r0), "=r"(r1), "=r"(r2), "=r"(r3) : "r"(a) : "memory");
}
DEVI float gelu_t(float x) {
  const float u = x * fmaf(x * x, 0.7978845608f * 0.044715f, 0.7978845608f);
  float th; asm("tanh.approx.f32 %0, %1;" : "=f"(th) : "f"(u));
  const float hx = 0.5f * x;
  return fmaf(hx, th, hx);
}
DEVI float bf_lo(uint32_t v) { return __uint_as_float(v << 16); }
DEVI float bf_hi(uint32_t v) { return __uint_as_float(v & 0xFFFF0000u); }
DEVI float bf_round(float x) { return bf_lo(pack_bf2(x, 0.f)); }

#define MPROF(i)
constexpr int MT = 104, MCTA = 20;
constexpr int M_B1 = 0, M_C1 = 14336, M_B2 = 100352, M_C2 = 13312, M_RING = 193536, M_ST = 226304, M_DUMP = M_ST + 896, M_BAR = M_ST + 1024;
constexpr int SMEM_MLP = M_BAR + 512;
enum { MB_F1 = 0, MB_E1 = 4, MB_F3 = 8, MB_E3 = 20, MB_HF = 32, MB_HE = 34, MB_G2 = 36, MB_X = 38 };
__host__ __device__ constexpr int m_slot3(int j) { return j < 4 ? M_RING + j * 8192 : M_B2 + 2 * M_C2 + (j - 4) * 8192; }

DEVI void ln_inplace(uint32_t sb, int nrows, int reps, int warp, int nw, int lane) {
#pragma unroll 1
  for (int r0 = warp; r0 < nrows; r0 += 3 * nw) {
    uint32_t a[3];
    float v[3][14];
#pragma unroll
    for (int k = 0; k < 3; k++) {
      const int r = r0 + nw * k < nrows ? r0 + nw * k : r0;
      a[k] = sb + M_B1 + r * 128 + ((((lane >> 2) ^ r) & 7) << 4) + (lane & 3) * 4;
#pragma unroll
      for (int i = 0; i < 7; i++) { uint32_t q; asm volatile("ld.shared.b32 %0, [%1];" : "=r"(q) : "r"(a[k] + i * M_C1) : "memory"); v[k][2 * i] = bf_lo(q); v[k][2 * i + 1] = bf_hi(q); }
    }
#pragma unroll 1
    for (int rp = 0; rp < reps; rp++) {
      float sm[3], vs[3];
#pragma unroll
      for (int k = 0; k < 3; k++) {
        sm[k] = 0;
#pragma unroll
        for (int i = 0; i < 14; i++) sm[k] += v[k][i];
      }
#pragma unroll
      for (int o = 16; o; o >>= 1)
#pragma unroll
        for (int k = 0; k < 3; k++) sm[k] += __shfl_xor_sync(0xffffffffu, sm[k], o);
#pragma unroll
      for (int k = 0; k < 3; k++) {
        vs[k] = 0;
#pragma unroll
        for (int i = 0; i < 14; i++) { v[k][i] -= sm[k] * (1.0f / DM); vs[k] += v[k][i] * v[k][i]; }
      }
#pragma unroll
      for (int o = 16; o; o >>= 1)
#pragma unroll
        for (int k = 0; k < 3; k++) vs[k] += __shfl_xor_sync(0xffffffffu, vs[k], o);
#pragma unroll
      for (int k = 0; k < 3; k++) {
        const float rs = rsqrtf(vs[k] * (1.0f / DM) + 1e-5f);
#pragma unroll
        for (int i = 0; i < 7; i++) { const uint32_t q = pack_bf2(v[k][2 * i] * rs, v[k][2 * i + 1] * rs); v[k][2 * i] = bf_lo(q); v[k][2 * i + 1] = bf_hi(q); }
      }
    }
#pragma unroll
    for (int k = 0; k < 3; k++)
#pragma unroll
      for (int i = 0; i < 7; i++) sts32(a[k] + i * M_C1, __byte_perm(__float_as_uint(v[k][2 * i]), __float_as_uint(v[k][2 * i + 1]), 0x7632));
  }
}
template <int NR, class F, class G>
DEVI void gemm448(float (&d)[NR], F mma, uint32_t bars, int n0, int nstep, uint32_t bdesc, uint32_t bstep, int lane, G after) {
#pragma unroll 1
  for (int kc = 0; kc < 7; kc++) {
    const int n = n0 + kc * nstep, sl = n & 3;
    mbar_wait(bars + (MB_F1 + sl) * 8, (n >> 2) & 1, 800);
    const uint32_t ad = desc_lo(M_RING) + sl * 512, bd = bdesc + kc * bstep;
    wg_fence();
#pragma unroll
    for (int j = 0; j < 4; j++) mma(d, mkdesc(ad + j * 128), mkdesc(bd + j * 2), kc > 0 || j > 0);
    wg_commit(); wg_wait0();
    mbar_arrive_if(lane == 0, bars + (MB_E1 + sl) * 8);
    after(n);
  }
}
DEVI void phase1_tile(uint32_t sb, uint32_t bars, int mt, int n0, int nstep, int t0, int w, int lane) {
  float d[56];
  gemm448(d, wgmma_n112, bars, n0, nstep, desc_lo(M_B1), M_C1 >> 4, lane, [](int) {});
  const int half = (lane >> 3) & 1, grp = (64 * mt + 16 * w + 8 * half) / 112;
  const int off = grp == 0 ? -1 : grp == 1 ? 1 : grp == 2 ? -2 : 2;
  const int c0 = t0 - 2 + 2 * (lane & 3);
#pragma unroll
  for (int q = 0; q < 7; q++) {
    uint32_t pk[4];
#pragma unroll
    for (int i = 0; i < 4; i++) {
      const int tk = c0 + 16 * q + 8 * (i >> 1);
      const float a = (tk >= 0 && tk < SEQ) ? gelu_t(d[8 * q + 2 * i]) : 0.f, b = (tk + 1 >= 0 && tk + 1 < SEQ) ? gelu_t(d[8 * q + 2 * i + 1]) : 0.f;
      pk[i] = pack_bf2(a, b);
    }
    const int row = 16 * q + (lane >> 4) * 8 + (lane & 7) - 2 - off;
    const uint32_t a = (row >= 0 && row < MT) ? sb + M_B2 + mt * M_C2 + row * 128 + (((2 * w + half) ^ (row & 7)) << 4) : sb + M_DUMP;
    stsm4t(a, pk[0], pk[1], pk[2], pk[3]);
  }
}
template <class G>
DEVI void phase2_tile(float (&d)[52], uint32_t sb, uint32_t bars, int mt, int n0, int nstep, int w, int lane, G after) {
  gemm448(d, wgmma_n104, bars, n0, nstep, desc_lo(M_B2), M_C2 >> 4, lane, after);
  const uint32_t a = sb + M_B1 + mt * M_C1 + ((lane >> 4) * 8 + (lane & 7)) * 128 + (((2 * w + ((lane >> 3) & 1)) ^ (lane & 7)) << 4);
#pragma unroll
  for (int q = 0; q < 7; q++) {
    uint32_t r[4];
    ldsm4t(r[0], r[1], r[2], r[3], a + q * 2048);
#pragma unroll
    for (int i = 0; i < 4; i++)
      if (8 * q + 2 * i < 52) {
        const uint32_t hs = pack_bf2(d[8 * q + 2 * i], d[8 * q + 2 * i + 1]);
        r[i] = pack_bf2(bf_lo(r[i]) + bf_lo(hs), bf_hi(r[i]) + bf_hi(hs));
        d[8 * q + 2 * i] = bf_lo(r[i]); d[8 * q + 2 * i + 1] = bf_hi(r[i]);
      }
    stsm4t(a + q * 2048, r[0], r[1], r[2], r[3]);
  }
}
template <class F>
DEVI void store_tile(const float (&d)[52], uint32_t base, int w, int lane, F f) {
  const uint32_t a = base + ((lane >> 4) * 8 + (lane & 7)) * 128 + (((2 * w + ((lane >> 3) & 1)) ^ (lane & 7)) << 4);
#pragma unroll
  for (int q = 0; q < 6; q++) {
    stsm4t(a + q * 2048, f(d[8 * q], d[8 * q + 1], 2 * q), f(d[8 * q + 2], d[8 * q + 3], 2 * q), f(d[8 * q + 4], d[8 * q + 5], 2 * q + 1), f(d[8 * q + 6], d[8 * q + 7], 2 * q + 1));
    __syncwarp();
  }
  stsm2t(a + 6 * 2048, f(d[48], d[49], 12), f(d[50], d[51], 12));
}
DEVI float sigm_f(float y) { return rcpf(1.0f + ex2(-1.4426950408889634f * y)); }
DEVI void store_gate(const float (&d)[52], uint32_t sb, int mt, int w, int lane) {
  store_tile(d, sb + M_B1 + mt * M_C1, w, lane, [&](float a, float b, int) { return pack_bf2(a, b); });
}
DEVI void gemm4_tile(float (&d)[52], int sl, uint32_t hd) {
  const uint32_t ad = (sl < 4 ? desc_lo(M_RING) : desc_lo(M_B2 + 2 * M_C2) - 4 * 512) + sl * 512;
#pragma unroll
  for (int j = 0; j < 4; j++) wgmma_n104(d, mkdesc(ad + j * 128), mkdesc(hd + j * 2), 1);
}
DEVI void mlp_finish(uint32_t sb, uint32_t bars, const __nv_bfloat16* __restrict__ x, __nv_bfloat16* __restrict__ out, int t0, int tid) {
  const int nch = min(MT, SEQ - t0) * 56;
  uint4* os = (uint4*)(out + (size_t)t0 * DM);
  mbar_wait(bars + MB_X * 8, 0, 830);
  bar_sync(1, 384);
#pragma unroll 1
  for (int i = tid; i < 7 * MT * 8; i += 256) {
    const int j = i / (MT * 8);
    const uint32_t ga = sb + M_B1 + j * M_C1 + (i - j * (MT * 8)) * 16;
    const uint4 gv = lds128(ga);
    auto f = [](uint32_t yy) { return pack_bf2(bf_lo(yy) * sigm_f(bf_lo(yy)), bf_hi(yy) * sigm_f(bf_hi(yy))); };
    sts128(ga, f(gv.x), f(gv.y), f(gv.z), f(gv.w));
  }
  bar_sync(4, 256);
#pragma unroll 1
  for (int pass = 0; pass < 2; pass++) {
    const uint4* ss = (const uint4*)((pass ? g_s : x) + (size_t)t0 * DM);
    if (pass) {
      if (tid == 0) MPROF(6);
      asm volatile("griddepcontrol.wait;" ::: "memory");
      if (tid == 0) MPROF(7);
    }
    int r = tid / 56, ch = tid - r * 56;
#pragma unroll 1
    for (int i0 = tid; i0 < (pass ? nch : 256); i0 += 8 * 256) {
      uint4 sv[8];
#pragma unroll
      for (int k = 0; k < 8; k++) sv[k] = __ldcg(ss + min(i0 + k * 256, nch - 1));
#pragma unroll
      for (int k = 0; k < 8; k++) {
        const uint32_t o = min(r, MT - 1) * 128 + (((ch ^ r) & 7) << 4);
        const uint4 gv = lds128(sb + M_B1 + (ch >> 3) * M_C1 + o), xx = lds128(sb + M_B2 + (ch >> 3) * M_C2 + o);
        auto f = [&](uint32_t xa, uint32_t sx, uint32_t gg) {
          const uint32_t pr = pack_bf2(bf_lo(gg) * bf_lo(sx), bf_hi(gg) * bf_hi(sx));
          return pack_bf2(bf_lo(xa) + bf_lo(pr), bf_hi(xa) + bf_hi(pr));
        };
        asm volatile("{.reg .pred p; setp.ne.u32 p, %5, 0; @p st.global.v4.b32 [%0], {%1,%2,%3,%4};}" ::"l"(os + i0 + k * 256), "r"(f(xx.x, sv[k].x, gv.x)),
                     "r"(f(xx.y, sv[k].y, gv.y)), "r"(f(xx.z, sv[k].z, gv.z)), "r"(f(xx.w, sv[k].w, gv.w)), "r"((uint32_t)(pass && i0 + k * 256 < nch)) : "memory");
        ch += 32; r += 4;
        if (ch >= 56) { ch -= 56; r++; }
      }
    }
  }
}

__global__ void __launch_bounds__(384, 1)
mlp_main(const __grid_constant__ CUtensorMap tm1, const __grid_constant__ CUtensorMap tm2, const __grid_constant__ CUtensorMap tm3,
         const __grid_constant__ CUtensorMap tm4, const __grid_constant__ CUtensorMap tmxa, const __grid_constant__ CUtensorMap tmxb,
         const unsigned char* w1, const unsigned char* w2, const unsigned char* w3, const unsigned char* w4,
         const __nv_bfloat16* __restrict__ x, __nv_bfloat16* __restrict__ out) {
  extern __shared__ __align__(1024) unsigned char smem_raw[];
  const uint32_t sb = smem_u32(smem_raw);
  if ((sb & 0xFFFFFF) != SB) fail(3);
  const int tid = threadIdx.x, warp = __reduce_min_sync(0xffffffffu, tid >> 5), lane = tid & 31, w = warp & 3, wg = warp >> 2;
  const uint32_t bars = sb + M_BAR;
  const int t0 = blockIdx.x * MT;
  if (tid == 0) MPROF(0);
  if (tid == 0) {
    for (int i = 0; i < 4; i++) { mbar_init(bars + (MB_F1 + i) * 8, 1); mbar_init(bars + (MB_E1 + i) * 8, 4); }
    for (int i = 0; i < 12; i++) { mbar_init(bars + (MB_F3 + i) * 8, 1); mbar_init(bars + (MB_E3 + i) * 8, 4); }
    for (int i = 0; i < 2; i++) { mbar_init(bars + (MB_HF + i) * 8, 4); mbar_init(bars + (MB_HE + i) * 8, 12); }
    mbar_init(bars + MB_G2 * 8, 4); mbar_init(bars + (MB_G2 + 1) * 8, 4); mbar_init(bars + MB_X * 8, 1);
    asm volatile("fence.mbarrier_init.release.cluster;" ::: "memory");
    mbar_expect(bars + MB_X * 8, 7 * M_C1);
    for (int j = 0; j < 7; j++) tma2d(sb + M_B1 + j * M_C1, &tmxa, j * 64, t0 - 2, bars + MB_X * 8);
  }
  if (warp == 1 && lane < 25) {
    const int i = lane * MCTA + blockIdx.x;
    const unsigned char* wp = i < 49 ? w1 + i * 8192 : i < 98 ? w2 + (i - 49) * 8192 : i < 294 ? w3 + (i - 98) * 8192 : w4 + (i - 294) * 8192;
    if (i < 490) asm volatile("cp.async.bulk.prefetch.L2.global [%0], 8192;" ::"l"(wp) : "memory");
  }
  __syncthreads();
  auto load_x = [&](uint32_t dst, uint32_t step) {
    mbar_expect(bars + MB_X * 8, 7 * M_C2);
    for (int j = 0; j < 7; j++) tma2d(dst + j * step, &tmxb, j * 64, t0, bars + MB_X * 8);
  };
  if (wg < 2) {
    asm volatile("setmaxnreg.inc.sync.aligned.u32 184;");
#pragma unroll 1
    for (int ph = 0; ph < 2; ph++) {
      mbar_wait(bars + MB_X * 8, ph, 831);
      ln_inplace(sb, ph ? MT : 112, 2 - ph, warp, 8, lane);
      fence_proxy_smem();
      bar_sync(4, 256);
      if (ph == 0) {
        if (wg == 0) MPROF(1);
#pragma unroll 1
        for (int r = 0; r < 4 - wg; r++) phase1_tile(sb, bars, r < 3 ? 2 * r + wg : 6, r < 3 ? 14 * r + wg : 42, r < 3 ? 2 : 1, t0, w, lane);
        fence_proxy_smem();
        bar_sync(4, 256);
        if (tid == 0) load_x(sb + M_B1, M_C1);
        __syncwarp();
        if (wg == 0) MPROF(2);
      }
    }
    bar_arrive(5, 384);
    if (wg == 0) MPROF(3);
    float y[3][52];
#pragma unroll
    for (int r = 0; r < 3; r++) phase2_tile(y[r], sb, bars, 3 * wg + r, 49 + 14 * r + wg, 2, w, lane, [](int) {});
    bar_sync(1, 384);
    auto load4 = [&](int f) {
      if (w == 0 && lane < 3) {
        const int sl = 3 * wg + lane;
        mbar_expect(bars + (MB_F3 + sl) * 8, 8192);
        tma2d(sb + m_slot3(sl), &tm4, sl * 64, f * 64, bars + (MB_F3 + sl) * 8);
      }
      __syncwarp();
    };
    load4(0);
    int rsl = 7, rph = 0;
    auto refill3 = [&](int f, int k0, int k1) {
#pragma unroll 1
      for (int kc = k0; kc < (f < 27 ? k1 : min(k1, 2)); kc++) {
        mbar_wait(bars + (MB_E3 + rsl) * 8, rph, 819);
        if (lane == 0) {
          mbar_expect(bars + (MB_F3 + rsl) * 8, 8192);
          tma2d(sb + m_slot3(rsl), &tm3, (kc < 2 ? f : f + 1) * 64, (kc < 2 ? kc + 5 : kc - 2) * 64, bars + (MB_F3 + rsl) * 8);
        }
        __syncwarp();
        if (++rsl == 12) { rsl = 7; rph ^= 1; }
      }
    };
    if (warp == 1) refill3(0, 0, 7);
#pragma unroll 1
    for (int f = 0; f < 28; f++) {
      const uint32_t hd = desc_lo(M_B2) + (f & 1) * (M_C2 >> 4);
      if (warp == 1 && f < 27) refill3(f + 1, 0, G2_AT);
#pragma unroll
      for (int i = 0; i < 3; i++) mbar_wait(bars + (MB_F3 + 3 * wg + i) * 8, f & 1, 811);
      mbar_wait(bars + (MB_HF + (f & 1)) * 8, (f >> 1) & 1, 811);
      if (f < 27) mbar_wait(bars + (MB_G2 + ((f + 1) & 1)) * 8, ((f + 1) >> 1) & 1, 818);
      wg_fence();
      gemm4_tile(y[0], 3 * wg, hd); gemm4_tile(y[1], 3 * wg + 1, hd); gemm4_tile(y[2], 3 * wg + 2, hd);
      wg_commit();
      if (warp == 1 && f < 27) refill3(f + 1, G2_AT, 7);
      wg_wait0();
      mbar_arrive_if(lane == 0, bars + (MB_HE + (f & 1)) * 8);
      bar_sync(2 + wg, 128);
      if (f < 27) load4(f + 1);
      if (warp == 5 && f < 27) mbar_wait(bars + (MB_HE + (f & 1)) * 8, (f >> 1) & 1, 823);
      if (warp == 5 && lane == 0 && f < 27) {
        mbar_expect(bars + (MB_F3 + 6) * 8, 8192);
        tma2d(sb + m_slot3(6), &tm4, 6 * 64, (f + 1) * 64, bars + (MB_F3 + 6) * 8);
      }
      __syncwarp();
    }
    bar_sync(1, 384);
#pragma unroll
    for (int i = 0; i < 3; i++) store_gate(y[i], sb, 3 * wg + i, w, lane);
    mlp_finish(sb, bars, x, out, t0, tid);
    if (tid == 0) MPROF(8);
  } else {
    asm volatile("setmaxnreg.dec.sync.aligned.u32 136;");
    auto issue1 = [&](int n0, int n1) {
#pragma unroll 1
      for (int n = n0; n < n1; n++) {
        const int m = n < 49 ? n : n - 49, r = m / 14, q = m - r * 14, kc = r < 3 ? q >> 1 : q;
        const int mt = r == 3 ? 6 : n < 49 ? 2 * r + (q & 1) : r + 3 * (q & 1);
        const int sl = n & 3;
        if (n >= 4) mbar_wait(bars + (MB_E1 + sl) * 8, ((n - 4) >> 2) & 1, 820);
        if (lane == 0) {
          mbar_expect(bars + (MB_F1 + sl) * 8, 8192);
          tma2d(sb + M_RING + sl * 8192, n < 49 ? &tm1 : &tm2, mt * 64, kc * 64, bars + (MB_F1 + sl) * 8);
        }
        __syncwarp();
      }
    };
    if (warp == 8) issue1(0, 95);
    bar_sync(5, 384);
    float y[52];
    phase2_tile(y, sb, bars, 6, 91, 1, w, lane, [&](int n) { if (warp == 8 && n + 4 < 98) issue1(n + 4, n + 5); });
    bar_sync(1, 384);
    auto load3 = [&](int sl, int f, int kc) {
      mbar_expect(bars + (MB_F3 + sl) * 8, 8192);
      tma2d(sb + m_slot3(sl), &tm3, f * 64, kc * 64, bars + (MB_F3 + sl) * 8);
    };
    auto load4 = [&](int f) {
      mbar_expect(bars + (MB_F3 + 6) * 8, 8192);
      tma2d(sb + m_slot3(6), &tm4, 6 * 64, f * 64, bars + (MB_F3 + 6) * 8);
    };
    MPROF(4);
    if (warp == 8 && lane < 5) load3(7 + lane, 0, lane);
    if (warp == 8 && lane == 5) load4(0);
    __syncwarp();
    ln_inplace(sb, MT, 1, w, 4, lane);
    fence_proxy_smem();
    bar_sync(6, 128);
    int sl = 7, ph = 0;
    auto chunk = [&](auto first_, const int f) {
      constexpr bool FIRST = decltype(first_)::value;
      float d[52];
      int psl = 0;
      wg_fence();
#pragma unroll
      for (int kc = 0; kc < 7; kc++) {
        mbar_wait(bars + (MB_F3 + sl) * 8, ph, 812);
        const uint32_t ad = desc_lo(M_B2 + 2 * M_C2) - 4 * 512 + sl * 512, bd = desc_lo(M_B1 + kc * M_C1);
#pragma unroll
        for (int j = 0; j < 4; j++) wgmma_n104(d, mkdesc(ad + j * 128), mkdesc(bd + j * 2), kc > 0 || j > 0);
        wg_commit();
        if (kc == G2_AT) mbar_arrive_if(lane == 0, bars + (MB_G2 + (f & 1)) * 8);
        if (kc > 0) {
          asm volatile("wgmma.wait_group.sync.aligned 1;" ::: "memory");
          mbar_arrive_if(lane == 0, bars + (MB_E3 + psl) * 8);
        }
        psl = sl;
        if (++sl == 12) { sl = 7; ph ^= 1; }
      }
      if (!FIRST) {
        mbar_wait(bars + (MB_HF + ((f - 1) & 1)) * 8, ((f - 1) >> 1) & 1, 816);
        mbar_wait(bars + (MB_F3 + 6) * 8, (f - 1) & 1, 810);
        gemm4_tile(y, 6, desc_lo(M_B2) + ((f - 1) & 1) * (M_C2 >> 4));
        wg_commit();
      }
      wg_wait0();
      if (!FIRST) mbar_arrive_if(lane == 0, bars + (MB_HE + ((f - 1) & 1)) * 8);
      mbar_arrive_if(lane == 0, bars + (MB_E3 + psl) * 8);
      if (f >= 2) mbar_wait(bars + (MB_HE + (f & 1)) * 8, ((f - 2) >> 1) & 1, 813);
      store_tile(d, sb + M_B2 + (f & 1) * M_C2, w, lane, [&](float a, float b, int) { return pack_bf2(gelu_t(a), gelu_t(b)); });
      fence_proxy_smem();
      __syncwarp();
      mbar_arrive_if(lane == 0, bars + (MB_HF + (f & 1)) * 8);
    };
    MPROF(16);
    chunk(True_(), 0);
#pragma unroll 1
    for (int f = 1; f < 28; f++) chunk(False_(), f);
    mbar_wait(bars + (MB_HF + 1) * 8, 1, 815);
    mbar_wait(bars + (MB_F3 + 6) * 8, 1, 810);
    wg_fence();
    gemm4_tile(y, 6, desc_lo(M_B2 + M_C2));
    wg_commit(); wg_wait0();
    bar_sync(1, 384);
    MPROF(5);
    if (tid == 256) load_x(sb + M_B2, M_C2);
    __syncwarp();
    store_gate(y, sb, 6, w, lane);
    bar_sync(1, 384);
  }
}

typedef CUresult (*EncFn)(CUtensorMap*, CUtensorMapDataType, cuuint32_t, void*, const cuuint64_t*, const cuuint64_t*, const cuuint32_t*, const cuuint32_t*,
                          CUtensorMapInterleave, CUtensorMapSwizzle, CUtensorMapL2promotion, CUtensorMapFloatOOBfill);
static void make_map(EncFn enc, CUtensorMap* m, const void* ptr, uint64_t cols, uint64_t rows, uint32_t bc, uint32_t br) {
  cuuint64_t dims[2] = {cols, rows}, strides[1] = {cols * 2};
  cuuint32_t box[2] = {bc, br}, es[2] = {1, 1};
  enc(m, CU_TENSOR_MAP_DATA_TYPE_BFLOAT16, 2, const_cast<void*>(ptr), dims, strides, box, es, CU_TENSOR_MAP_INTERLEAVE_NONE, CU_TENSOR_MAP_SWIZZLE_128B,
      CU_TENSOR_MAP_L2_PROMOTION_L2_256B, CU_TENSOR_MAP_FLOAT_OOB_FILL_NONE);
}

extern "C" void kernel_launch(void* const* d_in, const int* in_sizes, int n_in, void* d_out, int out_size) {
  const __nv_bfloat16* x = (const __nv_bfloat16*)d_in[0];
  const __nv_bfloat16* mem0 = (const __nv_bfloat16*)d_in[1];
  static EncFn enc = nullptr;
  static void* xn_ptr = nullptr;
  if (!enc) {
    cudaDriverEntryPointQueryResult qr;
    cudaGetDriverEntryPoint("cuTensorMapEncodeTiled", (void**)&enc, cudaEnableDefault, &qr);
    cudaGetSymbolAddress(&xn_ptr, g_xn);
    cudaFuncSetAttribute(attn_main, cudaFuncAttributeMaxDynamicSharedMemorySize, SMEM_MAIN + 6144);
    cudaFuncSetAttribute(attn_main, cudaFuncAttributeNonPortableClusterSizeAllowed, 1);
    cudaFuncSetAttribute(mlp_main, cudaFuncAttributeMaxDynamicSharedMemorySize, SMEM_MLP);
  }
  CUtensorMap tq, tk, tv, to, tx;
  make_map(enc, &tq, d_in[2], NH * DH, DM, 64, 64);
  make_map(enc, &tk, d_in[3], NH * DH, DM, 64, 32);
  make_map(enc, &tv, d_in[4], NH * DH, DM, 64, 32);
  make_map(enc, &to, d_in[5], DM, NH * DH, 64, 64);
  make_map(enc, &tx, xn_ptr, DM, SEQ, 64, 32);
  cudaLaunchConfig_t cfg = {};
  cfg.gridDim = dim3(NCTA); cfg.blockDim = dim3(NTHR); cfg.dynamicSmemBytes = SMEM_MAIN + 6144; cfg.stream = cudaStreamPerThread;
  cudaLaunchAttribute at[1];
  at[0].id = cudaLaunchAttributeClusterDimension; at[0].val.clusterDim.x = 16; at[0].val.clusterDim.y = 1; at[0].val.clusterDim.z = 1;
  cfg.attrs = at; cfg.numAttrs = 1;
  cudaLaunchKernelEx(&cfg, attn_main, tq, tk, tv, to, tx, x, mem0, 0);
  CUtensorMap t1, t2, t3, t4, txa, txb;
  make_map(enc, &txa, d_in[0], DM, SEQ, 64, 112);
  make_map(enc, &txb, d_in[0], DM, SEQ, 64, MT);
  make_map(enc, &t1, d_in[8], DM, DM, 64, 64);
  make_map(enc, &t2, d_in[9], DM, DM, 64, 64);
  make_map(enc, &t3, d_in[10], 4 * DM, DM, 64, 64);
  make_map(enc, &t4, d_in[11], DM, 4 * DM, 64, 64);
  cudaLaunchConfig_t cf2 = {};
  cf2.gridDim = dim3(MCTA); cf2.blockDim = dim3(384); cf2.dynamicSmemBytes = SMEM_MLP; cf2.stream = cudaStreamPerThread;
  cudaLaunchAttribute a2[1];
  a2[0].id = cudaLaunchAttributeProgrammaticStreamSerialization; a2[0].val.programmaticStreamSerializationAllowed = 1;
  cf2.attrs = a2; cf2.numAttrs = 1;
  cudaLaunchKernelEx(&cf2, mlp_main, t1, t2, t3, t4, txa, txb, (const unsigned char*)d_in[8], (const unsigned char*)d_in[9], (const unsigned char*)d_in[10],
                     (const unsigned char*)d_in[11], x, (__nv_bfloat16*)d_out);
}
```
